```python
import torch

def _softmax(x, axis=-1):
    return torch.softmax(x, dim=axis)
def _gelu(x):
    return torch.nn.functional.gelu(x, approximate="tanh")
def _silu(x):
    return torch.nn.functional.silu(x)
def _sigmoid(x):
    return torch.sigmoid(x)
def _layernorm(x, axis=-1, eps=1e-5):
    m = x.mean(dim=axis, keepdim=True)
    v = x.var(dim=axis, keepdim=True, unbiased=False)
    return (x - m) / torch.sqrt(v + eps)
def _scatter_add(tgt, idx, src, axis=0):
    return tgt.clone().index_add_(axis, idx, src)
def _segment_sum(src, seg, n):
    out = torch.zeros((n,) + src.shape[1:], dtype=src.dtype)
    return out.index_add_(0, seg, src)
def _pad(x, pw):
    flat = tuple(v for pair in reversed(pw) for v in pair)
    return torch.nn.functional.pad(x, flat)

kernel_name = 'sequential_preLN__grouped_kv_mqa__moe_arch_mod__prompt'

def setup_inputs():

    _w = (lambda a: (lambda t: t.to(torch.bfloat16) if t.is_floating_point() else t)(torch.as_tensor(a)))
    def _A_setup():
        B, S, D, H = 1, 2048, 576, 32
        Dh = D // H
        return {
            "x": _w((lambda *s: torch.randn(*s, dtype=torch.bfloat16) * 0.05)(B, S, D)),
            "wq": _w((lambda *s: torch.randn(*s, dtype=torch.bfloat16) * 0.05)(D, H * Dh)),
            "wk": _w((lambda *s: torch.randn(*s, dtype=torch.bfloat16) * 0.05)(D, Dh)),
            "wv": _w((lambda *s: torch.randn(*s, dtype=torch.bfloat16) * 0.05)(D, Dh)),
            "wo": _w((lambda *s: torch.randn(*s, dtype=torch.bfloat16) * 0.05)(H * Dh, D)),
        }
    _A_in = _A_setup()

    def _B_setup():
        B, S, D, F, C = 1, 2048, 576, 4608, 8
        return {
            "x": _w((lambda *s: torch.randn(*s, dtype=torch.bfloat16) * 0.05)(B, S, D)),
            "w_r": _w((lambda *s: torch.randn(*s, dtype=torch.bfloat16) * 0.05)(D)),
            "w_gate": _w((lambda *s: torch.randn(*s, dtype=torch.bfloat16) * 0.05)(D, F)),
            "w_up": _w((lambda *s: torch.randn(*s, dtype=torch.bfloat16) * 0.05)(D, F)),
            "w_down": _w((lambda *s: torch.randn(*s, dtype=torch.bfloat16) * 0.05)(F, D)),
        }
    _B_in = _B_setup()

    return {
        "A_x": _A_in["x"],
        "A_wq": _A_in["wq"],
        "A_wk": _A_in["wk"],
        "A_wv": _A_in["wv"],
        "A_wo": _A_in["wo"],
        "B_x": _B_in["x"],
        "B_w_r": _B_in["w_r"],
        "B_w_gate": _B_in["w_gate"],
        "B_w_up": _B_in["w_up"],
        "B_w_down": _B_in["w_down"],
    }

def reference(A_x, A_wq, A_wk, A_wv, A_wo, B_x, B_w_r, B_w_gate, B_w_up, B_w_down):
    def _A_ref(x, wq, wk, wv, wo):
        B, S, D = x.shape
        H = 32
        Dh = D // H
        q = (lambda x, *d: x.permute(*d))((x @ wq).reshape(B, S, H, Dh), 0, 2, 1, 3)
        k = x @ wk
        v = x @ wv
        scores = torch.einsum("bhqd,bkd->bhqk", q, k) * (Dh ** -0.5)
        p = _softmax(scores, axis=-1)
        o = torch.einsum("bhqk,bkd->bhqd", p, v)
        return (lambda x, *d: x.permute(*d))(o, 0, 2, 1, 3).reshape(B, S, H * Dh) @ wo

    def _B_ref(x, w_r, w_gate, w_up, w_down):
        B, S, D = x.shape
        C = 8
        r = x @ w_r
        idx = torch.argsort(-r, axis=-1)[:, :C]
        idx_e = (lambda x, n, axis: torch.repeat_interleave(x, n, dim=axis))(idx.reshape(B, C, 1), D, axis=2)
        x_sel = (lambda x, i, axis: torch.take_along_dim(x, i, dim=axis))(x, idx_e, axis=1)
        g = _silu(x_sel @ w_gate)
        u = x_sel @ w_up
        y = (g * u) @ w_down
        r_sel = _sigmoid((lambda x, i, axis: torch.take_along_dim(x, i, dim=axis))(r, idx, axis=1))
        y = y * r_sel.reshape(B, C, 1)
        b_off = (torch.arange(B) * S).reshape(B, 1)
        flat_idx = (idx + b_off).reshape(B * C)
        zero = (x * 0.0).reshape(B * S, D)
        upd = _scatter_add(zero, flat_idx, y.reshape(B * C, D), axis=0)
        return x + upd.reshape(B, S, D)

    x = A_x
    h = x + _A_ref(_layernorm(x, axis=-1), A_wq, A_wk, A_wv, A_wo)
    h2 = h + _B_ref(_layernorm(h, axis=-1), B_w_r, B_w_gate, B_w_up, B_w_down)
    return h2
```

```cpp
#include <cuda_runtime.h>
#include <cuda.h>
#include <cuda_bf16.h>
#include <cuda_fp16.h>
#include <stdint.h>

namespace {

constexpr int S_ = 2048, D_ = 576;
constexpr int NCTA = 130;
constexpr int NTHR = 512;

constexpr int SM_W = 0;
constexpr int SM_X = 73728;
constexpr int XSLOT = 21504;
constexpr int SM_WO = 0;
constexpr int SM_DOWN = 0;
constexpr int SM_GATE = 82944;
constexpr int SM_UP = 129024;
constexpr int SM_RING = 175104;
constexpr int SM_MISC = 226304;
constexpr int SM_TOTAL = SM_MISC + 4096;
constexpr int MB_FULLP = 0;
constexpr int MB_EMPTYP = 72;
constexpr int MB_FULL = 88;
constexpr int MB_EMPTY = 128;
constexpr int MB_WO = 168, MB_GU = 176, MB_DOWN = 184, MB_O1 = 192;
constexpr int MB_EMPTYO = 200;
constexpr int MB_FULLO = 248;
constexpr int MS_ST = 512;
constexpr int MS_RED = 1792;
constexpr int MS_CAND = 1920;
constexpr int MS_SEL = 2432;
constexpr int MS_ACT = 2560;
constexpr int FS_XS = 0;
constexpr int FS_HS = 9472;
constexpr int FS_PART = 18944;

__device__ float2   g_st0[S_];
__device__ uint32_t g_q[S_ * 288];
__device__ uint4    g_kv[256 * 40];
__device__ float    g_kvf[S_ * 36];
__device__ float    g_rsq[16];
__device__ __align__(1024) uint32_t g_o[S_ * 288];
__device__ __align__(16) uint32_t g_h[S_ * 288];
__device__ float4   g_st2[S_];
__device__ __align__(16) float g_y[D_ * 8];
__device__ unsigned g_cnt[64 * 32];
constexpr int C_ST = 0, C_P1 = 13, C_O = 14  , C_P3 = 46, C_FIN = 47, C_NUM = 48;
#define PROF_C(i)
#define PROF_T(i)

struct Params {
  const __nv_bfloat16 *x, *wq, *wk, *wv, *wr, *wdown;
  __nv_bfloat16* out;
};

__device__ __forceinline__ void wg_ss_n88_tA(float (&d)[44], uint64_t a, uint64_t b, int sc) {
  asm volatile("{ .reg .pred p; setp.ne.b32 p, %46, 0;\n"
    "wgmma.mma_async.sync.aligned.m64n88k16.f32.bf16.bf16 {%0, %1, %2, %3, %4, %5, %6, %7, %8, %9, %10, %11, %12, %13, %14, %15, %16, %17, %18, %19, %20, %21, %22, %23, %24, %25, %26, %27, %28, %29, %30, %31, %32, %33, %34, %35, %36, %37, %38, %39, %40, %41, %42, %43}, %44, %45, p, 1, 1, 1, 0; }"
    : "+f"(d[0]), "+f"(d[1]), "+f"(d[2]), "+f"(d[3]), "+f"(d[4]), "+f"(d[5]), "+f"(d[6]), "+f"(d[7]),
      "+f"(d[8]), "+f"(d[9]), "+f"(d[10]), "+f"(d[11]), "+f"(d[12]), "+f"(d[13]), "+f"(d[14]), "+f"(d[15]),
      "+f"(d[16]), "+f"(d[17]), "+f"(d[18]), "+f"(d[19]), "+f"(d[20]), "+f"(d[21]), "+f"(d[22]), "+f"(d[23]),
      "+f"(d[24]), "+f"(d[25]), "+f"(d[26]), "+f"(d[27]), "+f"(d[28]), "+f"(d[29]), "+f"(d[30]), "+f"(d[31]),
      "+f"(d[32]), "+f"(d[33]), "+f"(d[34]), "+f"(d[35]), "+f"(d[36]), "+f"(d[37]), "+f"(d[38]), "+f"(d[39]),
      "+f"(d[40]), "+f"(d[41]), "+f"(d[42]), "+f"(d[43])
    : "l"(a), "l"(b), "r"(sc));
}
__device__ __forceinline__ void wg_ss_n72_tB(float (&d)[36], uint64_t a, uint64_t b, int sc) {
  asm volatile("{ .reg .pred p; setp.ne.b32 p, %38, 0;\n"
    "wgmma.mma_async.sync.aligned.m64n72k16.f32.bf16.bf16 {%0, %1, %2, %3, %4, %5, %6, %7, %8, %9, %10, %11, %12, %13, %14, %15, %16, %17, %18, %19, %20, %21, %22, %23, %24, %25, %26, %27, %28, %29, %30, %31, %32, %33, %34, %35}, %36, %37, p, 1, 1, 0, 1; }"
    : "+f"(d[0]), "+f"(d[1]), "+f"(d[2]), "+f"(d[3]), "+f"(d[4]), "+f"(d[5]), "+f"(d[6]), "+f"(d[7]),
      "+f"(d[8]), "+f"(d[9]), "+f"(d[10]), "+f"(d[11]), "+f"(d[12]), "+f"(d[13]), "+f"(d[14]), "+f"(d[15]),
      "+f"(d[16]), "+f"(d[17]), "+f"(d[18]), "+f"(d[19]), "+f"(d[20]), "+f"(d[21]), "+f"(d[22]), "+f"(d[23]),
      "+f"(d[24]), "+f"(d[25]), "+f"(d[26]), "+f"(d[27]), "+f"(d[28]), "+f"(d[29]), "+f"(d[30]), "+f"(d[31]),
      "+f"(d[32]), "+f"(d[33]), "+f"(d[34]), "+f"(d[35])
    : "l"(a), "l"(b), "r"(sc));
}
__device__ __forceinline__ void wg_qk_n128(uint32_t (&d)[32], const uint32_t (&a)[4], uint64_t b, int sc) {
  asm volatile("{ .reg .pred p; setp.ne.b32 p, %37, 0;\n"
    "wgmma.mma_async.sync.aligned.m64n128k16.f16.f16.f16 {%0, %1, %2, %3, %4, %5, %6, %7, %8, %9, %10, %11, %12, %13, %14, %15, %16, %17, %18, %19, %20, %21, %22, %23, %24, %25, %26, %27, %28, %29, %30, %31}, {%32, %33, %34, %35}, %36, p, 1, 1, 0; }"
    : "+r"(d[0]), "+r"(d[1]), "+r"(d[2]), "+r"(d[3]), "+r"(d[4]), "+r"(d[5]), "+r"(d[6]), "+r"(d[7]),
      "+r"(d[8]), "+r"(d[9]), "+r"(d[10]), "+r"(d[11]), "+r"(d[12]), "+r"(d[13]), "+r"(d[14]), "+r"(d[15]),
      "+r"(d[16]), "+r"(d[17]), "+r"(d[18]), "+r"(d[19]), "+r"(d[20]), "+r"(d[21]), "+r"(d[22]), "+r"(d[23]),
      "+r"(d[24]), "+r"(d[25]), "+r"(d[26]), "+r"(d[27]), "+r"(d[28]), "+r"(d[29]), "+r"(d[30]), "+r"(d[31])
    : "r"(a[0]), "r"(a[1]), "r"(a[2]), "r"(a[3]), "l"(b), "r"(sc));
}
__device__ __forceinline__ void wg_pv_bf16(float (&d)[12], const uint32_t (&a)[4], uint64_t b, int sc) {
  asm volatile("{ .reg .pred p; setp.ne.b32 p, %17, 0;\n"
    "wgmma.mma_async.sync.aligned.m64n24k16.f32.bf16.bf16 {%0, %1, %2, %3, %4, %5, %6, %7, %8, %9, %10, %11}, {%12, %13, %14, %15}, %16, p, 1, 1, 1; }"
    : "+f"(d[0]), "+f"(d[1]), "+f"(d[2]), "+f"(d[3]), "+f"(d[4]), "+f"(d[5]), "+f"(d[6]), "+f"(d[7]),
      "+f"(d[8]), "+f"(d[9]), "+f"(d[10]), "+f"(d[11])
    : "r"(a[0]), "r"(a[1]), "r"(a[2]), "r"(a[3]), "l"(b), "r"(sc));
}
__device__ __forceinline__ void wg_pv_f16(float (&d)[12], const uint32_t (&a)[4], uint64_t b, int sc) {
  asm volatile("{ .reg .pred p; setp.ne.b32 p, %17, 0;\n"
    "wgmma.mma_async.sync.aligned.m64n24k16.f32.f16.f16 {%0, %1, %2, %3, %4, %5, %6, %7, %8, %9, %10, %11}, {%12, %13, %14, %15}, %16, p, 1, 1, 1; }"
    : "+f"(d[0]), "+f"(d[1]), "+f"(d[2]), "+f"(d[3]), "+f"(d[4]), "+f"(d[5]), "+f"(d[6]), "+f"(d[7]),
      "+f"(d[8]), "+f"(d[9]), "+f"(d[10]), "+f"(d[11])
    : "r"(a[0]), "r"(a[1]), "r"(a[2]), "r"(a[3]), "l"(b), "r"(sc));
}

__device__ __forceinline__ void wg_fence() { asm volatile("wgmma.fence.sync.aligned;" ::: "memory"); }
__device__ __forceinline__ void wg_commit() { asm volatile("wgmma.commit_group.sync.aligned;" ::: "memory"); }
template <int N> __device__ __forceinline__ void wg_wait() { asm volatile("wgmma.wait_group.sync.aligned %0;" ::"n"(N) : "memory"); }
template <int N> __device__ __forceinline__ void pin(float (&d)[N]) {
#pragma unroll
  for (int i = 0; i < N; i++) asm volatile("" : "+f"(d[i])::"memory");
}
template <int N> __device__ __forceinline__ void pin(uint32_t (&d)[N]) {
#pragma unroll
  for (int i = 0; i < N; i++) asm volatile("" : "+r"(d[i])::"memory");
}
__device__ __forceinline__ uint64_t dsc(uint32_t lo, uint32_t hi) { uint64_t r; asm("mov.b64 %0, {%1,%2};" : "=l"(r) : "r"(lo), "r"(hi)); return r; }
__device__ __forceinline__ void mbar_init(uint32_t a, int c) { asm volatile("mbarrier.init.shared::cta.b64 [%0], %1;" ::"r"(a), "r"(c) : "memory"); }
__device__ __forceinline__ void mbar_expect(uint32_t a, uint32_t b) { asm volatile("mbarrier.arrive.expect_tx.shared::cta.b64 _, [%0], %1;" ::"r"(a), "r"(b) : "memory"); }
__device__ __forceinline__ void mbar_arrive(uint32_t a) { asm volatile("mbarrier.arrive.shared::cta.b64 _, [%0];" ::"r"(a) : "memory"); }
__device__ __forceinline__ void mbar_wait(uint32_t a, uint32_t ph) {
  uint32_t ok;
  asm volatile("{.reg .pred p; mbarrier.try_wait.parity.shared::cta.b64 p, [%1], %2; selp.u32 %0,1,0,p;}" : "=r"(ok) : "r"(a), "r"(ph) : "memory");
  if (!ok) {
    int it = 0;
    do {
      asm volatile("{.reg .pred p; mbarrier.try_wait.parity.shared::cta.b64 p, [%1], %2; selp.u32 %0,1,0,p;}" : "=r"(ok) : "r"(a), "r"(ph) : "memory");
      if (++it > (1 << 24)) __trap();
    } while (!ok);
  }
}
__device__ __forceinline__ void bulk_g2s(uint32_t d, const void* s, uint32_t n, uint32_t m) {
  asm volatile("cp.async.bulk.shared::cluster.global.mbarrier::complete_tx::bytes [%0], [%1], %2, [%3];" ::"r"(d), "l"(s), "r"(n), "r"(m) : "memory");
}
__device__ __forceinline__ void tma2(uint32_t d, const CUtensorMap* m, int c0, int c1, uint32_t mb) {
  asm volatile("cp.async.bulk.tensor.2d.shared::cluster.global.mbarrier::complete_tx::bytes [%0], [%1, {%3,%4}], [%2];" ::"r"(d), "l"(m), "r"(mb), "r"(c0), "r"(c1) : "memory");
}
__device__ __forceinline__ void tma3(uint32_t d, const CUtensorMap* m, int c0, int c1, int c2, uint32_t mb) {
  asm volatile("cp.async.bulk.tensor.3d.shared::cluster.global.mbarrier::complete_tx::bytes [%0], [%1, {%3,%4,%5}], [%2];" ::"r"(d), "l"(m), "r"(mb), "r"(c0), "r"(c1), "r"(c2) : "memory");
}
__device__ __forceinline__ void l2_prefetch(const void* p, uint32_t n) { asm volatile("cp.async.bulk.prefetch.L2.global [%0], %1;" ::"l"(p), "r"(n) : "memory"); }
__device__ __forceinline__ void map_prefetch(const CUtensorMap* m) { asm volatile("prefetch.tensormap [%0];" ::"l"(m) : "memory"); }
__device__ __forceinline__ void fence_async() { asm volatile("fence.proxy.async;" ::: "memory"); }
__device__ __forceinline__ void fence_async_smem() { asm volatile("fence.proxy.async.shared::cta;" ::: "memory"); }
__device__ __forceinline__ void cnt_arrive(int c) { asm volatile("red.release.gpu.global.add.u32 [%0], 1;" ::"l"(&g_cnt[c * 32]) : "memory"); }
__device__ __forceinline__ void cnt_wait(int c, unsigned target) {
  unsigned v; int it = 0;
  do {
    asm volatile("ld.acquire.gpu.global.u32 %0, [%1];" : "=r"(v) : "l"(&g_cnt[c * 32]) : "memory");
    if (++it > (1 << 22)) __trap();
  } while (v < target);
}
__device__ __forceinline__ void bar_sync(int id, int n) { asm volatile("bar.sync %0, %1;" ::"r"(id), "r"(n) : "memory"); }
__device__ __forceinline__ void bar_arrive(int id, int n) { asm volatile("bar.arrive %0, %1;" ::"r"(id), "r"(n) : "memory"); }
__device__ __forceinline__ float bf_lo(uint32_t w) { return __uint_as_float(w << 16); }
__device__ __forceinline__ float bf_hi(uint32_t w) { return __uint_as_float(w & 0xffff0000u); }
__device__ __forceinline__ uint32_t pk_bf(float lo, float hi) { uint32_t r; asm("cvt.rn.bf16x2.f32 %0, %1, %2;" : "=r"(r) : "f"(hi), "f"(lo)); return r; }
__device__ __forceinline__ uint32_t pk_h(float lo, float hi) { uint32_t r; asm("cvt.rn.f16x2.f32 %0, %1, %2;" : "=r"(r) : "f"(hi), "f"(lo)); return r; }
__device__ __forceinline__ uint32_t movm(uint32_t a) { uint32_t d; asm volatile("movmatrix.sync.aligned.m8n8.trans.b16 %0, %1;" : "=r"(d) : "r"(a)); return d; }
__device__ __forceinline__ void ldsm4(uint32_t (&r)[4], uint32_t a) { asm volatile("ldmatrix.sync.aligned.m8n8.x4.shared.b16 {%0,%1,%2,%3}, [%4];" : "=r"(r[0]), "=r"(r[1]), "=r"(r[2]), "=r"(r[3]) : "r"(a) : "memory"); }
__device__ __forceinline__ void ldsm4t(uint32_t (&r)[4], uint32_t a) { asm volatile("ldmatrix.sync.aligned.m8n8.x4.trans.shared.b16 {%0,%1,%2,%3}, [%4];" : "=r"(r[0]), "=r"(r[1]), "=r"(r[2]), "=r"(r[3]) : "r"(a) : "memory"); }
__device__ __forceinline__ void ldsm2t(uint32_t (&r)[2], uint32_t a) { asm volatile("ldmatrix.sync.aligned.m8n8.x2.trans.shared.b16 {%0,%1}, [%2];" : "=r"(r[0]), "=r"(r[1]) : "r"(a) : "memory"); }
__device__ __forceinline__ void mma16(float (&d)[4], const uint32_t (&a)[4], uint32_t b0, uint32_t b1) {
  asm volatile("mma.sync.aligned.m16n8k16.row.col.f32.bf16.bf16.f32 {%0,%1,%2,%3}, {%4,%5,%6,%7}, {%8,%9}, {%0,%1,%2,%3};"
               : "+f"(d[0]), "+f"(d[1]), "+f"(d[2]), "+f"(d[3]) : "r"(a[0]), "r"(a[1]), "r"(a[2]), "r"(a[3]), "r"(b0), "r"(b1));
}
__device__ __forceinline__ void mma8(float (&d)[4], const uint32_t (&a)[2], uint32_t b0) {
  asm volatile("mma.sync.aligned.m16n8k8.row.col.f32.bf16.bf16.f32 {%0,%1,%2,%3}, {%4,%5}, {%6}, {%0,%1,%2,%3};"
               : "+f"(d[0]), "+f"(d[1]), "+f"(d[2]), "+f"(d[3]) : "r"(a[0]), "r"(a[1]), "r"(b0));
}

constexpr float QSCALE = 0.23570226039551584f * 1.4426950408889634f;
constexpr uint32_t H_CA = 0x2cb7u, H_CB = 0x5a9eu;
constexpr uint32_t ZK = 0x47014701u;
constexpr float L_MIN = 8.0f;

__device__ __forceinline__ void exp_tile(const uint32_t (&s)[32], uint32_t (&p)[8][4], uint32_t zk, uint32_t half) {
#pragma unroll
  for (int g = 0; g < 8; g++) {
#pragma unroll
    for (int i = 0; i < 4; i++) {
      uint32_t y = s[g * 4 + i], r;
      if ((g & 3) == 0) {
        asm("ex2.approx.f16x2 %0, %1;" : "=r"(r) : "r"(y));
      } else {
        uint32_t z, m, e;
        asm("mad.lo.u32 %0, %1, -2, %2;" : "=r"(z) : "r"(y), "r"(zk));
        asm("lop3.b32 %0, %1, 0x007f007f, %2, 0xEA;" : "=r"(m) : "r"(z), "r"(half));
        asm("and.b32 %0, %1, 0xff81ff81;" : "=r"(e) : "r"(z));
        asm("fma.rn.bf16x2 %0, %1, %2, %3;" : "=r"(r) : "r"(z), "r"(m), "r"(e));
      }
      p[g][i] = r;
    }
  }
}
__device__ __forceinline__ void pv_tile(float (&o)[12], const uint32_t (&p)[8][4], uint32_t vlo) {
#pragma unroll
  for (int g = 0; g < 8; g++) {
    if ((g & 3) == 0) wg_pv_f16(o, p[g], dsc(vlo + g * 80, 8), 1);
    else wg_pv_bf16(o, p[g], dsc(vlo + g * 80, 8), 1);
  }
}

__device__ __noinline__ void exact_tile(const __nv_bfloat16* x, const __nv_bfloat16* wq, int tok0, int head) {
  const int t = threadIdx.x & 127, tok = tok0 + (t >> 1), hf = t & 1;
  const float2 st = __ldcg(&g_st0[tok]);
  float q[18], o[18];
#pragma unroll
  for (int d = 0; d < 18; d++) { q[d] = 0.f; o[d] = 0.f; }
  for (int k = hf * 288; k < hf * 288 + 288; k++) {
    const float xn = (__bfloat162float(x[tok * D_ + k]) - st.x) * st.y;
    const uint32_t* w = reinterpret_cast<const uint32_t*>(wq + k * D_ + head * 18);
#pragma unroll
    for (int j = 0; j < 9; j++) { uint32_t v = w[j]; q[2 * j] += xn * bf_lo(v); q[2 * j + 1] += xn * bf_hi(v); }
  }
#pragma unroll
  for (int d = 0; d < 18; d++) q[d] = (q[d] + __shfl_xor_sync(0xffffffffu, q[d], 1)) * QSCALE;
  float m = -INFINITY, l = 0.f;
  for (int j = hf * 1024; j < hf * 1024 + 1024; j++) {
    float kv[36];
#pragma unroll
    for (int i = 0; i < 9; i++) {
      const float4 v = __ldcg(reinterpret_cast<const float4*>(g_kvf + j * 36) + i);
      kv[4 * i] = v.x; kv[4 * i + 1] = v.y; kv[4 * i + 2] = v.z; kv[4 * i + 3] = v.w;
    }
    float s = 0.f;
#pragma unroll
    for (int d = 0; d < 18; d++) s += q[d] * kv[d];
    const float mn = fmaxf(m, s), a = exp2f(m - mn), p = exp2f(s - mn);
    m = mn; l = l * a + p;
#pragma unroll
    for (int d = 0; d < 18; d++) o[d] = o[d] * a + p * kv[18 + d];
  }
  const float m2 = __shfl_xor_sync(0xffffffffu, m, 1), mn = fmaxf(m, m2), a = exp2f(m - mn);
  l *= a; l += __shfl_xor_sync(0xffffffffu, l, 1);
  const float inv = 1.f / l;
#pragma unroll
  for (int d = 0; d < 18; d++) { o[d] *= a; o[d] = (o[d] + __shfl_xor_sync(0xffffffffu, o[d], 1)) * inv; }
  if (hf == 0) {
#pragma unroll
    for (int j = 0; j < 9; j++) g_o[tok * 288 + head * 9 + j] = pk_bf(o[2 * j], o[2 * j + 1]);
  }
}

template <int W>
__device__ __forceinline__ void p1_epilogue(const float (&d)[44], uint8_t* sm, int grp, int slice, int warp, int lane) {
  const float2* st = reinterpret_cast<const float2*>(sm + SM_MISC + MS_ST) + W * 80;
  const float cs0 = d[W ? 40 : 0], cs1 = d[W ? 42 : 2];
  const int c = lane & 3, r = lane >> 2;
  if (slice < 9) {
#pragma unroll
    for (int i = 0; i < 10; i++) {
      const float4 s2 = *reinterpret_cast<const float4*>(st + i * 8 + 2 * c);
      const int b = (W ? i : i + 1) * 4;
      const float f0 = s2.y * (QSCALE / 512.f), f1 = s2.w * (QSCALE / 512.f);
      uint2 v;
      v.x = movm(pk_h((d[b] - s2.x * cs0) * f0, (d[b + 1] - s2.z * cs0) * f1));
      v.y = movm(pk_h((d[b + 2] - s2.x * cs1) * f0, (d[b + 3] - s2.z * cs1) * f1));
      const int tok = grp * 160 + W * 80 + i * 8 + r;
      if (tok < S_) *reinterpret_cast<uint2*>(&g_q[tok * 288 + slice * 32 + warp * 8 + c * 2]) = v;
    }
  } else if (warp < 3) {
    float* stg = reinterpret_cast<float*>(sm + SM_W);
#pragma unroll
    for (int i = 0; i < 10; i++) {
      const float4 s2 = *reinterpret_cast<const float4*>(st + i * 8 + 2 * c);
      const int b = (W ? i : i + 1) * 4;
      float* p = stg + (W * 80 + i * 8 + 2 * c) * 52 + warp * 16 + r;
      p[0] = (d[b] - s2.x * cs0) * s2.y;      p[52] = (d[b + 1] - s2.z * cs0) * s2.w;
      p[8] = (d[b + 2] - s2.x * cs1) * s2.y;  p[60] = (d[b + 3] - s2.z * cs1) * s2.w;
    }
  }
}

__global__ void __launch_bounds__(NTHR, 1)
fused_kernel(const __grid_constant__ CUtensorMap m_x, const __grid_constant__ CUtensorMap m_wq,
             const __grid_constant__ CUtensorMap m_wo, const __grid_constant__ CUtensorMap m_g,
             const __grid_constant__ CUtensorMap m_u, const __grid_constant__ CUtensorMap m_d,
             const __grid_constant__ CUtensorMap m_o, const Params P) {
  extern __shared__ __align__(1024) uint8_t sm[];
  const uint32_t sa = (uint32_t)__cvta_generic_to_shared(sm);
  const uint32_t mb = sa + SM_MISC;
  const int tid = threadIdx.x, lane = tid & 31, wid = tid >> 5, wg = tid >> 7, warp = wid & 3;
  const int b = blockIdx.x;
  PROF_T(0); PROF_C(1);

  {
    const int grp = b / 10, slice = b - grp * 10;
    if (tid == 0) {
      for (int i = 0; i < 9; i++) mbar_init(mb + MB_FULLP + 8 * i, 1);
      for (int i = 0; i < 2; i++) mbar_init(mb + MB_EMPTYP + 8 * i, 8);
      for (int i = 0; i < 5; i++) { mbar_init(mb + MB_FULL + 8 * i, 1); mbar_init(mb + MB_EMPTY + 8 * i, 16); }
      for (int i = 0; i < 6; i++) mbar_init(mb + MB_EMPTYO + 8 * i, 4);
      for (int i = 0; i < 18; i++) mbar_init(mb + MB_FULLO + 8 * i, 1);
      mbar_init(mb + MB_WO, 1); mbar_init(mb + MB_GU, 1); mbar_init(mb + MB_DOWN, 1); mbar_init(mb + MB_O1, 16);
      asm volatile("fence.mbarrier_init.release.cluster;" ::: "memory");
      fence_async_smem();
      const uint32_t bytes = 20480 + (slice < 9 ? 8192 : 0);
#pragma unroll
      for (int i = 0; i < 9; i++) {
        mbar_expect(mb + MB_FULLP + 8 * i, bytes);
        if (i < 7) tma2(sa + SM_X + 1024 + i * XSLOT, &m_x, i * 64, grp * 160, mb + MB_FULLP + 8 * i);
        if (slice < 9) tma2(sa + SM_W + i * 8192, &m_wq, slice * 64, i * 64, mb + MB_FULLP + 8 * i);
      }
      mbar_expect(mb + MB_WO, 82944);
      mbar_expect(mb + MB_GU, 92160);
    }
    if (tid == 32 && b < 128) l2_prefetch(reinterpret_cast<const uint8_t*>(P.wq) + b * 5184, 5184);
    uint4 xv[3];
    const int row = b * 16 + wid;
    if (b < 128 && lane < 24) {
#pragma unroll
      for (int i = 0; i < 3; i++) xv[i] = __ldg(reinterpret_cast<const uint4*>(P.x + row * D_) + i * 24 + lane);
    } else {
#pragma unroll
      for (int i = 0; i < 3; i++) xv[i] = make_uint4(0, 0, 0, 0);
    }
    if (slice == 9) {
      uint32_t wv_[21];
#pragma unroll
      for (int i = 0; i < 21; i++) {
        const int e = tid + i * NTHR;
        wv_[i] = e < 5184 ? __ldg(reinterpret_cast<const uint32_t*>(P.wk) + e)
               : e < 10368 ? __ldg(reinterpret_cast<const uint32_t*>(P.wv) + e - 5184) : 0u;
      }
#pragma unroll
      for (int i = 0; i < 21; i++) {
        const int e = tid + i * NTHR;
        if (e < 10368) {
          const int isv = e >= 5184, ee = e - isv * 5184, k = ee / 9, w = ee - k * 9 + isv * 9;
          *reinterpret_cast<uint32_t*>(sm + SM_W + k * 128 + (((w >> 2) ^ (k & 7)) << 4) + (w & 3) * 4) = wv_[i];
        }
      }
    }
    *reinterpret_cast<uint4*>(sm + SM_X + (tid >> 6) * XSLOT + (tid & 63) * 16) = make_uint4(0x3f803f80u, 0x3f803f80u, 0x3f803f80u, 0x3f803f80u);
    if (tid < 2) *reinterpret_cast<uint32_t*>(sm + SM_MISC + MS_RED + tid * 4) = 0u;
    if (b < 128) {
      if (tid < 16) g_st2[b * 16 + tid] = make_float4(0.f, 0.f, 0.f, 0.f);
      else if (tid >= 32 && tid < 41) reinterpret_cast<float4*>(g_y)[b * 9 + tid - 32] = make_float4(0.f, 0.f, 0.f, 0.f);
      const uint32_t* w = reinterpret_cast<const uint32_t*>(xv);
      float s = 0.f;
#pragma unroll
      for (int i = 0; i < 12; i++) s += bf_lo(w[i]) + bf_hi(w[i]);
#pragma unroll
      for (int o = 16; o; o >>= 1) s += __shfl_xor_sync(0xffffffffu, s, o);
      const float mean = s * (1.f / D_);
      float v = 0.f;
#pragma unroll
      for (int i = 0; i < 12; i++) { const float a = bf_lo(w[i]) - mean, c = bf_hi(w[i]) - mean; v += a * a + c * c; }
      if (lane >= 24) v = 0.f;
#pragma unroll
      for (int o = 16; o; o >>= 1) v += __shfl_xor_sync(0xffffffffu, v, o);
      if (lane == 0) g_st0[row] = make_float2(mean, rsqrtf(v * (1.f / D_) + 1e-5f));
    }
    fence_async_smem();
    __syncthreads();
    PROF_C(2);
    if (wg < 2) {
      float d[44];
#pragma unroll
      for (int i = 0; i < 44; i++) d[i] = 0.f;
      pin(d);
      const uint32_t alo = ((sa + SM_W) >> 4) | (1u << 16), hi = 64u | (1u << 30);
      const uint32_t blo = ((sa + SM_X + wg * 11264) >> 4) | (1u << 16);
#pragma unroll
      for (int kt = 0; kt < 9; kt++) {
        mbar_wait(mb + MB_FULLP + 8 * kt, 0);
        wg_fence();
#pragma unroll
        for (int ks = 0; ks < 4; ks++)
          wg_ss_n88_tA(d, dsc(alo + kt * 512 + ks * 128, hi), dsc(blo + (kt % 7) * (XSLOT / 16) + ks * 2, hi), 1);
        wg_commit();
        if (kt == 1 || kt == 2) { wg_wait<1>(); if (lane == 0) mbar_arrive(mb + MB_EMPTYP + 8 * (kt - 1)); }
      }
      wg_wait<0>(); pin(d);
      PROF_C(3);
      bar_sync(1, 384);
      if (wg == 0) p1_epilogue<0>(d, sm, grp, slice, warp, lane); else p1_epilogue<1>(d, sm, grp, slice, warp, lane);
    } else if (wg == 2) {
      if (tid == 256) {
#pragma unroll
        for (int i = 0; i < 2; i++) {
          mbar_wait(mb + MB_EMPTYP + 8 * i, 0);
          tma2(sa + SM_X + 1024 + i * XSLOT, &m_x, (7 + i) * 64, grp * 160, mb + MB_FULLP + 8 * (7 + i));
        }
        map_prefetch(&m_wo); map_prefetch(&m_g); map_prefetch(&m_u); map_prefetch(&m_d); map_prefetch(&m_o);
      }
    } else {
      if (tid == 384) { if (b < 128) cnt_arrive(C_ST + grp); cnt_wait(C_ST + grp, grp == 12 ? 8 : 10); }
      bar_sync(2, 128);
      for (int i = tid - 384; i < 160; i += 128) {
        const int tok = grp * 160 + i;
        reinterpret_cast<float2*>(sm + SM_MISC + MS_ST)[i] = tok < S_ ? __ldcg(&g_st0[tok]) : make_float2(0.f, 0.f);
      }
      bar_arrive(1, 384);
    }
    if (slice == 9) {
      __syncthreads();
      const float* stg = reinterpret_cast<const float*>(sm + SM_W);
      const int ntok = grp == 12 ? 128 : 160;
      float rmax = 0.f; uint32_t big = 0;
      for (int j = tid; j < ntok * 5; j += NTHR) {
        const int g8 = j / 40, rem = j - g8 * 40, cc = rem >> 3, tl = g8 * 8 + (rem & 7), tok = grp * 160 + tl;
        const float* p = stg + tl * 52;
        const bool mu = ((tok >> 4) & 3) == 0;
        const float ks = mu ? 512.f : -1.f / 512.f;
        uint4 o;
        if (cc < 2) {
          p += cc * 8;
          o = make_uint4(pk_h(p[0] * ks, p[1] * ks), pk_h(p[2] * ks, p[3] * ks), pk_h(p[4] * ks, p[5] * ks), pk_h(p[6] * ks, p[7] * ks));
        } else if (cc == 2) {
          float n2 = 0.f;
#pragma unroll
          for (int i = 0; i < 18; i++) n2 += p[i] * p[i];
          float vm = 0.f;
#pragma unroll
          for (int i = 0; i < 18; i++) { const float a = fabsf(p[18 + i]); vm = fmaxf(vm, a); big |= (a >= 0.0078125f ? 1u : 0u) << i; }
          if (!(n2 <= 14400.f) || !(vm <= 30000.f)) n2 = INFINITY;
          rmax = fmaxf(rmax, n2);
          o.x = pk_h(p[16] * ks, p[17] * ks);
          o.y = mu ? (0xe000u | (H_CB << 16)) : 0x1800u;
          o.z = mu ? pk_h(p[34], p[35]) : pk_bf(p[34], p[35]);
          o.w = mu ? 0x3c00u : 0x3f80u;
        } else {
          p += 18 + (cc - 3) * 8;
          o = mu ? make_uint4(pk_h(p[0], p[1]), pk_h(p[2], p[3]), pk_h(p[4], p[5]), pk_h(p[6], p[7]))
                 : make_uint4(pk_bf(p[0], p[1]), pk_bf(p[2], p[3]), pk_bf(p[4], p[5]), pk_bf(p[6], p[7]));
        }
        g_kv[grp * 800 + j] = o;
      }
      for (int j = tid; j < ntok * 9; j += NTHR) {
        const int tl = j / 9, q4 = j - tl * 9;
        reinterpret_cast<float4*>(g_kvf)[grp * 1440 + j] = *reinterpret_cast<const float4*>(stg + tl * 52 + q4 * 4);
      }
      const uint32_t rm = __reduce_max_sync(0xffffffffu, __float_as_uint(rmax));
      big = __reduce_or_sync(0xffffffffu, big);
      uint32_t* red = reinterpret_cast<uint32_t*>(sm + SM_MISC + MS_RED);
      if (lane == 0) { atomicMax(&red[0], rm); atomicOr(&red[1], big); }
    }
    fence_async_smem();
    __syncthreads();
    PROF_C(4);
    if (tid == 0) {
      if (slice == 9) {
        const uint32_t* red = reinterpret_cast<const uint32_t*>(sm + SM_MISC + MS_RED);
        g_rsq[grp] = red[1] == 0x3ffffu ? __uint_as_float(red[0]) : INFINITY;
      }
      fence_async();
      cnt_arrive(C_P1);
    }
    if (b >= 128) return;
  }

  const int tg = b >> 3, hg = b & 7;
  const int c = lane & 3, r = lane >> 2;
  if (tid == 0) {
    cnt_wait(C_P1, NCTA);
    fence_async();
#pragma unroll
    for (int i = 0; i < 3; i++) {
      mbar_expect(mb + MB_FULL + 8 * i, 10240);
      bulk_g2s(sa + SM_RING + i * 10240, g_kv + i * 640, 10240, mb + MB_FULL + 8 * i);
    }
  }
  __syncthreads();
  PROF_C(5);
  {
    const int head = hg * 4 + wg;
    float rk;
    {
      const float v = lane < 13 ? __ldcg(&g_rsq[lane]) : 0.f;
      rk = sqrtf(__uint_as_float(__reduce_max_sync(0xffffffffu, __float_as_uint(v)))) * 1.002f + 2.5e-4f;
    }
    uint32_t zk = ZK, half = 0x3f003f00u;
    asm volatile("" : "+r"(zk), "+r"(half));
    int slot = 0; uint32_t ph = 0;
#pragma unroll 1
    for (int pass = 0; pass < 2; pass++) {
      const int tok0 = tg * 128 + pass * 64;
      uint32_t q0[4], q1[4];
      bool bad;
      {
        const uint32_t* qr = g_q + (tok0 + warp * 16 + r) * 288;
        const int p0 = head * 9 + c, p1 = p0 + 4, p2 = head * 9 + 8;
        const int a0 = (p0 & ~7) + ((p0 & 3) << 1) + ((p0 >> 2) & 1);
        const int a1 = (p1 & ~7) + ((p1 & 3) << 1) + ((p1 >> 2) & 1);
        const int a2 = (p2 & ~7) + ((p2 & 3) << 1) + ((p2 >> 2) & 1);
        q0[0] = __ldcg(qr + a0); q0[1] = __ldcg(qr + 8 * 288 + a0);
        q0[2] = __ldcg(qr + a1); q0[3] = __ldcg(qr + 8 * 288 + a1);
        q1[0] = c == 0 ? __ldcg(qr + a2) : 0u; q1[1] = c == 0 ? __ldcg(qr + 8 * 288 + a2) : 0u;
        q1[2] = 0u; q1[3] = 0u;
        float n[2];
#pragma unroll
        for (int i = 0; i < 2; i++) {
          const float2 u = __half22float2(*reinterpret_cast<const __half2*>(&q0[i]));
          const float2 v = __half22float2(*reinterpret_cast<const __half2*>(&q0[i + 2]));
          const float2 w = __half22float2(*reinterpret_cast<const __half2*>(&q1[i]));
          float t = u.x * u.x + u.y * u.y + v.x * v.x + v.y * v.y + w.x * w.x + w.y * w.y;
          t += __shfl_xor_sync(0xffffffffu, t, 1);
          t += __shfl_xor_sync(0xffffffffu, t, 2);
          n[i] = sqrtf(t) * 1.0001f;
        }
        const float m0 = n[0] * rk + 0.05f / 512.f, m1 = n[1] * rk + 0.05f / 512.f;
        bad = !(fmaxf(m0, m1) <= 60.f / 512.f) || !(fmaxf(n[0], n[1]) <= 120.f / 512.f) || m0 != m0 || m1 != m1;
        if (c == 1) {
          q1[0] = (uint32_t)__half_as_ushort(__float2half_ru(m0)) | (H_CA << 16);
          q1[1] = (uint32_t)__half_as_ushort(__float2half_ru(m1)) | (H_CA << 16);
        }
      }
      float o[12]; uint32_t s[32];
#pragma unroll
      for (int i = 0; i < 12; i++) o[i] = 0.f;
#pragma unroll
      for (int i = 0; i < 32; i++) s[i] = 0u;
      pin(o); pin(s); pin(q0); pin(q1);
      const uint32_t kbase = ((sa + SM_RING) >> 4) | (8u << 16), vbase = ((sa + SM_RING + 256) >> 4) | (40u << 16);
      mbar_wait(mb + MB_FULL + 8 * slot, ph);
      wg_fence();
      wg_qk_n128(s, q0, dsc(kbase + slot * 640, 40), 0);
      wg_qk_n128(s, q1, dsc(kbase + slot * 640 + 16, 40), 1);
      wg_commit(); wg_wait<0>(); pin(s);
#pragma unroll 1
      for (int it = 0; it < 16; it++) {
        uint32_t p[8][4];
        exp_tile(s, p, zk, half);
        const int cur = slot;
        if (++slot == 5) { slot = 0; ph ^= 1; }
        if (it < 15) {
          mbar_wait(mb + MB_FULL + 8 * slot, ph);
          wg_fence();
          pv_tile(o, p, vbase + cur * 640);
          wg_qk_n128(s, q0, dsc(kbase + slot * 640, 40), 0);
          wg_qk_n128(s, q1, dsc(kbase + slot * 640 + 16, 40), 1);
          wg_commit();
        } else {
          wg_fence();
          pv_tile(o, p, vbase + cur * 640);
          wg_commit();
        }
        const int t = pass * 16 + it;
        if ((t & 3) == wg && (tid & 127) == 0) {
          const int n = t + 3;
          if (n < 32) {
            const int ns = n % 5;
            if (n >= 5) mbar_wait(mb + MB_EMPTY + 8 * ns, ((n / 5) - 1) & 1);
            mbar_expect(mb + MB_FULL + 8 * ns, 10240);
            bulk_g2s(sa + SM_RING + ns * 10240, g_kv + (n & 15) * 640, 10240, mb + MB_FULL + 8 * ns);
          }
          const int fc = (b >> 1) * 72 + (b & 1) * 32;
          if (t < 9) tma3(sa + SM_WO + t * 9216, &m_wo, 0, t * 64, hg * 9, mb + MB_WO);
          else if (t < 18) tma2(sa + SM_GATE + (t - 9) * 5120, &m_g, fc, (t - 9) * 64, mb + MB_GU);
          else if (t < 27) tma2(sa + SM_UP + (t - 18) * 5120, &m_u, fc, (t - 18) * 64, mb + MB_GU);
          else if (t == 27) l2_prefetch(P.wdown + fc * D_, 46080);
          if (t == 20) { mbar_wait(mb + MB_O1, 0); fence_async(); cnt_arrive(C_O + tg * 2); }
        }
        __syncwarp();
        wg_wait<0>(); pin(s); pin(o);
        if (lane == 0) mbar_arrive(mb + MB_EMPTY + 8 * cur);
      }
      const float l0 = __shfl_sync(0xffffffffu, o[0], lane | 3), l1 = __shfl_sync(0xffffffffu, o[2], lane | 3);
      bad = bad || !(l0 >= L_MIN) || !(l1 >= L_MIN) || !(l0 < 1e30f) || !(l1 < 1e30f);
      int anybad;
      asm volatile("{.reg .pred p,q; setp.ne.u32 p, %1, 0; barrier.red.or.pred q, %2, 128, p; selp.u32 %0,1,0,q;}" : "=r"(anybad) : "r"((int)bad), "r"(4 + wg) : "memory");
      if (anybad) {
        exact_tile(P.x, P.wq, tok0, head);
      } else {
        const float i0 = 1.f / l0, i1 = 1.f / l1;
        uint32_t* op = g_o + (tok0 + warp * 16 + r) * 288 + head * 9;
        op[c] = pk_bf(o[4] * i0, o[5] * i0);               op[8 * 288 + c] = pk_bf(o[6] * i1, o[7] * i1);
        op[4 + c] = pk_bf(o[8] * i0, o[9] * i0);           op[8 * 288 + 4 + c] = pk_bf(o[10] * i1, o[11] * i1);
        if (c == 2) { op[8] = pk_bf(o[0] * i0, o[1] * i0); op[8 * 288 + 8] = pk_bf(o[2] * i1, o[3] * i1); }
      }
      if (pass == 0) { __syncwarp(); if (lane == 0) mbar_arrive(mb + MB_O1); PROF_C(6); }
    }
  }
  __syncthreads();
  PROF_C(7);

  uint32_t hreg[18];
  const int htok = tg * 128 + (wg & 1) * 64 + warp * 16 + r;
  float wsum = 0.f;
  if (wg < 2) {
    uint32_t wr[9];
#pragma unroll
    for (int i = 0; i < 9; i++) {
      hreg[2 * i] = __ldg(reinterpret_cast<const uint32_t*>(P.x) + htok * 288 + hg * 36 + i * 4 + c);
      hreg[2 * i + 1] = __ldg(reinterpret_cast<const uint32_t*>(P.x) + (htok + 8) * 288 + hg * 36 + i * 4 + c);
      wr[i] = __ldg(reinterpret_cast<const uint32_t*>(P.wr) + hg * 36 + i * 4 + c);
    }
    float d[36];
#pragma unroll
    for (int i = 0; i < 36; i++) d[i] = 0.f;
    pin(d);
    mbar_wait(mb + MB_WO, 0);
    const uint32_t alo = ((sa + SM_RING) >> 4) | (1u << 16), ahi = 64u | (1u << 30);
    const uint32_t blo = ((sa + SM_WO) >> 4) | (8u << 16), bhi = 64u;
    int os = wg * 3;
#pragma unroll
    for (int kt = 0; kt < 9; kt++) {
      mbar_wait(mb + MB_FULLO + 8 * (wg * 9 + kt), 0);
      wg_fence();
#pragma unroll
      for (int ks = 0; ks < 4; ks++)
        wg_ss_n72_tB(d, dsc(alo + os * 512 + ks * 2, ahi), dsc(blo + kt * 576 + ks * 16, bhi), 1);
      wg_commit();
      if (kt > 0) { wg_wait<1>(); if (lane == 0) mbar_arrive(mb + MB_EMPTYO + 8 * (os == 0 ? 5 : os - 1)); }
      if (++os == 6) os = 0;
    }
    wg_wait<0>(); pin(d);
    if (lane == 0) mbar_arrive(mb + MB_EMPTYO + 8 * (os == 0 ? 5 : os - 1));
    PROF_C(8);
    float s0 = 0.f, s1 = 0.f, v0 = 0.f, v1 = 0.f, t0 = 0.f, t1 = 0.f;
#pragma unroll
    for (int i = 0; i < 9; i++) {
      const uint32_t h0 = pk_bf(bf_lo(hreg[2 * i]) + d[4 * i], bf_hi(hreg[2 * i]) + d[4 * i + 1]);
      const uint32_t h1 = pk_bf(bf_lo(hreg[2 * i + 1]) + d[4 * i + 2], bf_hi(hreg[2 * i + 1]) + d[4 * i + 3]);
      hreg[2 * i] = h0; hreg[2 * i + 1] = h1;
      const float a0 = bf_lo(h0), a1 = bf_hi(h0), b0 = bf_lo(h1), b1 = bf_hi(h1), w0 = bf_lo(wr[i]), w1 = bf_hi(wr[i]);
      s0 += a0 + a1; v0 += a0 * a0 + a1 * a1; t0 += a0 * w0 + a1 * w1;
      s1 += b0 + b1; v1 += b0 * b0 + b1 * b1; t1 += b0 * w0 + b1 * w1;
      g_h[htok * 288 + hg * 36 + i * 4 + c] = h0;
      g_h[(htok + 8) * 288 + hg * 36 + i * 4 + c] = h1;
    }
#pragma unroll
    for (int o = 1; o < 4; o <<= 1) {
      s0 += __shfl_xor_sync(0xffffffffu, s0, o); v0 += __shfl_xor_sync(0xffffffffu, v0, o); t0 += __shfl_xor_sync(0xffffffffu, t0, o);
      s1 += __shfl_xor_sync(0xffffffffu, s1, o); v1 += __shfl_xor_sync(0xffffffffu, v1, o); t1 += __shfl_xor_sync(0xffffffffu, t1, o);
    }
    if (c < 2)
      asm volatile("red.global.add.v4.f32 [%0], {%1,%2,%3,%4};" ::"l"(&g_st2[htok + c * 8]), "f"(c ? s1 : s0), "f"(c ? v1 : v0), "f"(c ? t1 : t0), "f"(0.f) : "memory");
    bar_sync(4 + wg, 128);
    if ((tid & 127) == 0) cnt_arrive(C_P3);
  } else if (tid == 256) {
    cnt_wait(C_O + tg * 2, 8);
    fence_async();
#pragma unroll 1
    for (int n = 0; n < 18; n++) {
      const int ns = n % 6;
      if (n == 9) { cnt_wait(C_O + tg * 2 + 1, 8); fence_async(); }
      if (n >= 6) mbar_wait(mb + MB_EMPTYO + 8 * ns, ((n / 6) - 1) & 1);
      mbar_expect(mb + MB_FULLO + 8 * n, 8192);
      tma2(sa + SM_RING + ns * 8192, &m_o, (n % 9) * 64, tg * 128 + (n / 9) * 64, mb + MB_FULLO + 8 * n);
    }
    mbar_wait(mb + MB_EMPTYO + 8 * 5, 0);
    mbar_expect(mb + MB_DOWN, 46080);
    tma3(sa + SM_DOWN, &m_d, 0, (b >> 1) * 72 + (b & 1) * 32, 0, mb + MB_DOWN);
  } else if (tid == 384) {
    fence_async();
    cnt_arrive(C_O + tg * 2 + 1);
  }
  __syncwarp();
  {
#pragma unroll
    for (int i = 0; i < 9; i++) { const uint32_t w = __ldg(reinterpret_cast<const uint32_t*>(P.wr) + i * 32 + lane); wsum += bf_lo(w) + bf_hi(w); }
#pragma unroll
    for (int o = 16; o; o >>= 1) wsum += __shfl_xor_sync(0xffffffffu, wsum, o);
  }
  uint32_t af[12][4];
  {
    mbar_wait(mb + MB_GU, 0);
    const int w15 = wid < 15 ? wid : 0, mt = w15 % 5, kq = w15 / 5, mi = lane >> 3;
    const uint32_t a = sa + ((mi & 1) ? SM_UP : SM_GATE) + (kq * 192 + (mi >> 1) * 8 + (lane & 7)) * 80 + mt * 16;
#pragma unroll
    for (int i = 0; i < 12; i++) ldsm4t(af[i], a + i * 1280);
  }
  if (tid == 480) cnt_wait(C_P3, 256);
  __syncthreads();
  PROF_C(9);

  {
    float4 st[4];
#pragma unroll
    for (int i = 0; i < 4; i++) st[i] = __ldcg(&g_st2[tid + i * NTHR]);
    float4 sa0, sa1;
    if (wg < 2) { sa0 = __ldcg(&g_st2[htok]); sa1 = __ldcg(&g_st2[htok + 8]); }
    uint32_t key[4]; float mean[4], rstd[4], rr[4];
#pragma unroll
    for (int i = 0; i < 4; i++) {
      mean[i] = st[i].x * (1.f / D_);
      rstd[i] = rsqrtf(fmaxf(st[i].y * (1.f / D_) - mean[i] * mean[i], 0.f) + 1e-5f);
      rr[i] = (st[i].z - mean[i] * wsum) * rstd[i];
      const uint32_t u = __float_as_uint(rr[i]);
      key[i] = (((u >> 31) ? ~u : (u | 0x80000000u)) & ~0x7ffu) | (uint32_t)(2047 - (tid + i * NTHR));
    }
    uint32_t* cand = reinterpret_cast<uint32_t*>(sm + SM_MISC + MS_CAND);
    uint32_t k0 = key[0], k1 = key[1], k2 = key[2], k3 = key[3], mine = 0;
#pragma unroll
    for (int j = 0; j < 8; j++) {
      const uint32_t m = __reduce_max_sync(0xffffffffu, max(max(k0, k1), max(k2, k3)));
      if (k0 == m) k0 = 0; if (k1 == m) k1 = 0; if (k2 == m) k2 = 0; if (k3 == m) k3 = 0;
      if (lane == j) mine = m;
    }
    if (lane < 8) cand[wid * 8 + lane] = mine;
    __syncthreads();
    const uint4 cv = reinterpret_cast<const uint4*>(cand)[lane];
    k0 = cv.x; k1 = cv.y; k2 = cv.z; k3 = cv.w;
    float4* sel = reinterpret_cast<float4*>(sm + SM_MISC + MS_SEL);
    const int gt = tid / 72;
    uint32_t mk = 0, mk7 = 0;
#pragma unroll
    for (int j = 0; j < 8; j++) {
      const uint32_t m = __reduce_max_sync(0xffffffffu, max(max(k0, k1), max(k2, k3)));
      if (k0 == m) k0 = 0; if (k1 == m) k1 = 0; if (k2 == m) k2 = 0; if (k3 == m) k3 = 0;
      if (gt == j) mk = m;
      if (j == 7) mk7 = m;
#pragma unroll
      for (int i = 0; i < 4; i++)
        if (key[i] == m) sel[j] = make_float4(mean[i], rstd[i], 1.f / (1.f + __expf(-rr[i])), __int_as_float(tid + i * NTHR));
    }
    PROF_C(10);
    const int ch = tid - gt * 72;
    const uint4 hv = __ldcg(reinterpret_cast<const uint4*>(g_h) + (2047 - (mk & 0x7ff)) * 72 + ch);
    uint4 hv2 = make_uint4(0, 0, 0, 0);
    if (tid < 64) hv2 = __ldcg(reinterpret_cast<const uint4*>(g_h) + (2047 - (mk7 & 0x7ff)) * 72 + 8 + tid);
    if (wg < 2) {
      const float m0 = sa0.x * (1.f / D_), m1 = sa1.x * (1.f / D_);
      const float r0 = rsqrtf(fmaxf(sa0.y * (1.f / D_) - m0 * m0, 0.f) + 1e-5f), r1 = rsqrtf(fmaxf(sa1.y * (1.f / D_) - m1 * m1, 0.f) + 1e-5f);
      uint32_t* op = reinterpret_cast<uint32_t*>(P.out) + htok * 288 + hg * 36 + c;
#pragma unroll
      for (int i = 0; i < 9; i++) {
        const float a0 = bf_lo(hreg[2 * i]), a1 = bf_hi(hreg[2 * i]), b0 = bf_lo(hreg[2 * i + 1]), b1 = bf_hi(hreg[2 * i + 1]);
        op[i * 4] = pk_bf(a0 + (a0 - m0) * r0, a1 + (a1 - m0) * r0);
        op[8 * 288 + i * 4] = pk_bf(b0 + (b0 - m1) * r1, b1 + (b1 - m1) * r1);
      }
    }
    __syncthreads();
    uint8_t* fs = sm + SM_RING;
    {
      const float4 se = sel[gt];
      const uint32_t w[4] = {hv.x, hv.y, hv.z, hv.w};
      uint32_t n[4];
#pragma unroll
      for (int i = 0; i < 4; i++) n[i] = pk_bf((bf_lo(w[i]) - se.x) * se.y, (bf_hi(w[i]) - se.x) * se.y);
      *reinterpret_cast<uint4*>(fs + FS_XS + gt * 1168 + ch * 16) = make_uint4(n[0], n[1], n[2], n[3]);
      *reinterpret_cast<uint4*>(fs + FS_HS + gt * 1168 + ch * 16) = hv;
      if (tid < 64) {
        const float4 s7 = sel[7];
        const uint32_t w2[4] = {hv2.x, hv2.y, hv2.z, hv2.w};
#pragma unroll
        for (int i = 0; i < 4; i++) n[i] = pk_bf((bf_lo(w2[i]) - s7.x) * s7.y, (bf_hi(w2[i]) - s7.x) * s7.y);
        *reinterpret_cast<uint4*>(fs + FS_XS + 7 * 1168 + (8 + tid) * 16) = make_uint4(n[0], n[1], n[2], n[3]);
        *reinterpret_cast<uint4*>(fs + FS_HS + 7 * 1168 + (8 + tid) * 16) = hv2;
      }
    }
    __syncthreads();
    PROF_C(11);
    float4* part = reinterpret_cast<float4*>(fs + FS_PART);
    if (wid < 15) {
      float d0[4] = {0.f, 0.f, 0.f, 0.f}, d1[4] = {0.f, 0.f, 0.f, 0.f};
      const uint32_t xa = sa + SM_RING + FS_XS + (lane & 7) * 1168 + (wid / 5) * 384 + (lane >> 3) * 16;
#pragma unroll
      for (int i = 0; i < 6; i++) {
        uint32_t bb[4];
        ldsm4(bb, xa + i * 64);
        mma16(d0, af[2 * i], bb[0], bb[1]);
        mma16(d1, af[2 * i + 1], bb[2], bb[3]);
      }
      part[wid * 32 + lane] = make_float4(d0[0] + d1[0], d0[1] + d1[1], d0[2] + d1[2], d0[3] + d1[3]);
    }
    uint32_t da[3][2][4], db[3][2];
    mbar_wait(mb + MB_DOWN, 0);
    if (wid < 12) {
#pragma unroll
      for (int j = 0; j < 3; j++) {
        const int mt = wid * 3 + j, mi = lane >> 3, f = (mi >> 1) * 8 + (lane & 7), chunk = (mt & 3) * 2 + (mi & 1);
        const uint32_t a = sa + SM_DOWN + (mt >> 2) * 5120 + ((chunk ^ (lane & 7)) << 4);
        ldsm4t(da[j][0], a + f * 128);
        ldsm4t(da[j][1], a + (f + 16) * 128);
        ldsm2t(db[j], a + (32 + (lane & 7)) * 128);
      }
    }
    __syncthreads();
    uint32_t* act = reinterpret_cast<uint32_t*>(sm + SM_MISC + MS_ACT);
    if (wid < 5) {
      const float4 p0 = part[wid * 32 + lane], p1 = part[(wid + 5) * 32 + lane], p2 = part[(wid + 10) * 32 + lane];
      const float g0 = p0.x + p1.x + p2.x, g1 = p0.y + p1.y + p2.y, u0 = p0.z + p1.z + p2.z, u1 = p0.w + p1.w + p2.w;
      uint32_t a = pk_bf(g0 / (1.f + __expf(-g0)) * u0, g1 / (1.f + __expf(-g1)) * u1);
      if (wid == 0 && (b & 1)) a = 0u;
      act[wid * 32 + lane] = movm(a);
    }
    __syncthreads();
    if (wid < 12) {
      uint32_t bb[5];
#pragma unroll
      for (int i = 0; i < 5; i++) bb[i] = act[i * 32 + lane];
#pragma unroll
      for (int j = 0; j < 3; j++) {
        float d[4] = {0.f, 0.f, 0.f, 0.f};
        mma16(d, da[j][0], bb[0], bb[1]);
        mma16(d, da[j][1], bb[2], bb[3]);
        mma8(d, db[j], bb[4]);
        float* yp = g_y + ((wid * 3 + j) * 16 + r) * 8 + 2 * c;
        asm volatile("red.global.add.v2.f32 [%0], {%1,%2};" ::"l"(yp), "f"(d[0]), "f"(d[1]) : "memory");
        asm volatile("red.global.add.v2.f32 [%0], {%1,%2};" ::"l"(yp + 64), "f"(d[2]), "f"(d[3]) : "memory");
      }
    }
    __syncthreads();
    PROF_C(12);
    uint32_t* flag = reinterpret_cast<uint32_t*>(sm + SM_MISC + MS_RED);
    if (tid == 0) {
      unsigned old;
      asm volatile("atom.acq_rel.gpu.global.add.u32 %0, [%1], 1;" : "=r"(old) : "l"(&g_cnt[C_FIN * 32]) : "memory");
      flag[2] = old;
    }
    __syncthreads();
    PROF_C(13);
    if (flag[2] == 127) {
      if (tid < 288) {
        float4 y[4];
#pragma unroll
        for (int i = 0; i < 4; i++) y[i] = __ldcg(reinterpret_cast<const float4*>(g_y) + tid * 4 + i);
        const float ya[8] = {y[0].x, y[0].y, y[0].z, y[0].w, y[1].x, y[1].y, y[1].z, y[1].w};
        const float yb[8] = {y[2].x, y[2].y, y[2].z, y[2].w, y[3].x, y[3].y, y[3].z, y[3].w};
#pragma unroll
        for (int j = 0; j < 8; j++) {
          const float4 se = sel[j];
          const uint32_t h = *reinterpret_cast<const uint32_t*>(fs + FS_HS + j * 1168 + tid * 4);
          const float a0 = bf_lo(h), a1 = bf_hi(h);
          reinterpret_cast<uint32_t*>(P.out)[__float_as_int(se.w) * 288 + tid] =
              pk_bf(a0 + (a0 - se.x) * se.y + se.z * ya[j], a1 + (a1 - se.x) * se.y + se.z * yb[j]);
        }
      } else if (tid >= 320 && tid < 320 + C_NUM) {
        g_cnt[(tid - 320) * 32] = 0u;
      }
    }
    PROF_C(14); PROF_T(15);
  }
}

typedef CUresult (*EncodeFn)(CUtensorMap*, CUtensorMapDataType, cuuint32_t, void*, const cuuint64_t*, const cuuint64_t*,
                             const cuuint32_t*, const cuuint32_t*, CUtensorMapInterleave, CUtensorMapSwizzle,
                             CUtensorMapL2promotion, CUtensorMapFloatOOBfill);

void make_map(EncodeFn enc, CUtensorMap* m, const void* p, int rank, cuuint64_t d0, cuuint64_t d1, cuuint64_t d2,
              cuuint64_t s1, cuuint64_t s2, cuuint32_t b0, cuuint32_t b1, cuuint32_t b2, CUtensorMapSwizzle sw) {
  const cuuint64_t gd[3] = {d0, d1, d2}, gs[2] = {s1, s2};
  const cuuint32_t bx[3] = {b0, b1, b2}, es[3] = {1, 1, 1};
  enc(m, CU_TENSOR_MAP_DATA_TYPE_BFLOAT16, rank, const_cast<void*>(p), gd, gs, bx, es, CU_TENSOR_MAP_INTERLEAVE_NONE, sw,
      CU_TENSOR_MAP_L2_PROMOTION_L2_128B, CU_TENSOR_MAP_FLOAT_OOB_FILL_NONE);
}

}

extern "C" void kernel_launch(void* const* d_in, const int* in_sizes, int n_in, void* d_out, int out_size) {
  (void)in_sizes; (void)n_in; (void)out_size;
  void* fn = nullptr;
  cudaDriverEntryPointQueryResult qr;
  cudaGetDriverEntryPoint("cuTensorMapEncodeTiled", &fn, cudaEnableDefault, &qr);
  EncodeFn enc = (EncodeFn)fn;
  void* o_ptr = nullptr;
  cudaGetSymbolAddress(&o_ptr, g_o);
  CUtensorMap mx, mwq, mwo, mg, mu, md, mo;
  make_map(enc, &mx, d_in[0], 2, 576, 2048, 1, 1152, 0, 64, 160, 1, CU_TENSOR_MAP_SWIZZLE_128B);
  make_map(enc, &mwq, d_in[1], 2, 576, 576, 1, 1152, 0, 64, 64, 1, CU_TENSOR_MAP_SWIZZLE_128B);
  make_map(enc, &mwo, d_in[4], 3, 8, 576, 72, 1152, 16, 8, 64, 9, CU_TENSOR_MAP_SWIZZLE_NONE);
  make_map(enc, &mg, d_in[7], 2, 4608, 576, 1, 9216, 0, 40, 64, 1, CU_TENSOR_MAP_SWIZZLE_NONE);
  make_map(enc, &mu, d_in[8], 2, 4608, 576, 1, 9216, 0, 40, 64, 1, CU_TENSOR_MAP_SWIZZLE_NONE);
  make_map(enc, &md, d_in[9], 3, 64, 4608, 9, 1152, 128, 64, 40, 9, CU_TENSOR_MAP_SWIZZLE_128B);
  make_map(enc, &mo, o_ptr, 2, 576, 2048, 1, 1152, 0, 64, 64, 1, CU_TENSOR_MAP_SWIZZLE_128B);
  Params P;
  P.x = (const __nv_bfloat16*)d_in[0]; P.wq = (const __nv_bfloat16*)d_in[1]; P.wk = (const __nv_bfloat16*)d_in[2];
  P.wv = (const __nv_bfloat16*)d_in[3]; P.wr = (const __nv_bfloat16*)d_in[6]; P.wdown = (const __nv_bfloat16*)d_in[9];
  P.out = (__nv_bfloat16*)d_out;
  cudaFuncSetAttribute(fused_kernel, cudaFuncAttributeMaxDynamicSharedMemorySize, SM_TOTAL);
  fused_kernel<<<NCTA, NTHR, SM_TOTAL, cudaStreamPerThread>>>(mx, mwq, mwo, mg, mu, md, mo, P);
}
```

```cpp
#include <cuda_runtime.h>
#include <cuda.h>
#include <cuda_bf16.h>
#include <cuda_fp16.h>
#include <stdint.h>

namespace {

constexpr int S_ = 2048, D_ = 576;
constexpr int NTHR = 512;

constexpr int SM_W = 0;
constexpr int SM_X = 73728;
constexpr int XSLOT = 23552, KSLOT = 12288;
constexpr int SM1_MISC = 216064;
constexpr int SM1_TOTAL = SM1_MISC + 1536;
constexpr int SM_WO = 0;
constexpr int SM_QB = 55296;
constexpr int SM_XT = 82944;
constexpr int SM_GATE = 101376;
constexpr int SM_UP = 147456;
constexpr int SM_DOWN = 193536;
constexpr int SM_KV = 66560;
constexpr int SM_MISC = 230400;
constexpr int SM_TOTAL = SM_MISC + 2048;
constexpr int MB_KV = 0  , MB_Q = 16  , MB_WO = 32, MB_XT = 40, MB_GU = 48, MB_DOWN = 56, MB_O1 = 64, MB_G3 = 72, MB_QC = 80, MB_KV1 = 88;
constexpr int MS_K = 144;
constexpr int MS_BAD = 160;
constexpr int MS_PROG = 320;
constexpr int MS_MAX = 192;
constexpr int MS_SEL = 256;
constexpr int MS_RSQ = 1024;
constexpr int MS_WR = 1600;
constexpr int MS_ROW = 896;
constexpr int FS_TAB = 10240;
constexpr int FS_XS = FS_TAB + 16384;
constexpr int FS_HS = FS_XS + 9472;
constexpr int FS_PART = FS_HS + 9472;
constexpr int FS_ACT = FS_PART + 8192;
constexpr int FS_RED = FS_ACT + 640;

struct Scratch {
  float4   st2[S_];
  float2   st0[S_];
  unsigned cnt[33 * 32];
  float    rsq[224];
  uint4    kv[256 * 40];
  uint4    yp[128 * 576];
  uint4    o[32 * 36 * 128];
  uint32_t h[S_ * 288];
  uint4    q[9 * S_ * 8];
  uint4    kvb[256 * 40];
  uint32_t fix[128 * 16 * 160];
};
__device__ __align__(1024) Scratch g_s;
#define PROF_C(i, t)
#define PROF_T(i, t)

__device__ __forceinline__ void wg_ss_n96_tA(float (&d)[48], uint64_t a, uint64_t b, int sc) {
  asm volatile("{ .reg .pred p; setp.ne.b32 p, %50, 0;\n"
    "wgmma.mma_async.sync.aligned.m64n96k16.f32.bf16.bf16 {%0, %1, %2, %3, %4, %5, %6, %7, %8, %9, %10, %11, %12, %13, %14, %15, %16, %17, %18, %19, %20, %21, %22, %23, %24, %25, %26, %27, %28, %29, %30, %31, %32, %33, %34, %35, %36, %37, %38, %39, %40, %41, %42, %43, %44, %45, %46, %47}, %48, %49, p, 1, 1, 1, 0; }"
    : "+f"(d[0]), "+f"(d[1]), "+f"(d[2]), "+f"(d[3]), "+f"(d[4]), "+f"(d[5]), "+f"(d[6]), "+f"(d[7]),
      "+f"(d[8]), "+f"(d[9]), "+f"(d[10]), "+f"(d[11]), "+f"(d[12]), "+f"(d[13]), "+f"(d[14]), "+f"(d[15]),
      "+f"(d[16]), "+f"(d[17]), "+f"(d[18]), "+f"(d[19]), "+f"(d[20]), "+f"(d[21]), "+f"(d[22]), "+f"(d[23]),
      "+f"(d[24]), "+f"(d[25]), "+f"(d[26]), "+f"(d[27]), "+f"(d[28]), "+f"(d[29]), "+f"(d[30]), "+f"(d[31]),
      "+f"(d[32]), "+f"(d[33]), "+f"(d[34]), "+f"(d[35]), "+f"(d[36]), "+f"(d[37]), "+f"(d[38]), "+f"(d[39]),
      "+f"(d[40]), "+f"(d[41]), "+f"(d[42]), "+f"(d[43]), "+f"(d[44]), "+f"(d[45]), "+f"(d[46]), "+f"(d[47])
    : "l"(a), "l"(b), "r"(sc));
}
__device__ __forceinline__ void wg_rs_n72_tB(float (&d)[36], const uint32_t (&a)[4], uint64_t b, int sc) {
  asm volatile("{ .reg .pred p; setp.ne.b32 p, %41, 0;\n"
    "wgmma.mma_async.sync.aligned.m64n72k16.f32.bf16.bf16 {%0, %1, %2, %3, %4, %5, %6, %7, %8, %9, %10, %11, %12, %13, %14, %15, %16, %17, %18, %19, %20, %21, %22, %23, %24, %25, %26, %27, %28, %29, %30, %31, %32, %33, %34, %35}, {%36, %37, %38, %39}, %40, p, 1, 1, 1; }"
    : "+f"(d[0]), "+f"(d[1]), "+f"(d[2]), "+f"(d[3]), "+f"(d[4]), "+f"(d[5]), "+f"(d[6]), "+f"(d[7]),
      "+f"(d[8]), "+f"(d[9]), "+f"(d[10]), "+f"(d[11]), "+f"(d[12]), "+f"(d[13]), "+f"(d[14]), "+f"(d[15]),
      "+f"(d[16]), "+f"(d[17]), "+f"(d[18]), "+f"(d[19]), "+f"(d[20]), "+f"(d[21]), "+f"(d[22]), "+f"(d[23]),
      "+f"(d[24]), "+f"(d[25]), "+f"(d[26]), "+f"(d[27]), "+f"(d[28]), "+f"(d[29]), "+f"(d[30]), "+f"(d[31]),
      "+f"(d[32]), "+f"(d[33]), "+f"(d[34]), "+f"(d[35])
    : "r"(a[0]), "r"(a[1]), "r"(a[2]), "r"(a[3]), "l"(b), "r"(sc));
}
__device__ __forceinline__ void wg_qk_n128(uint32_t (&d)[32], const uint32_t (&a)[4], uint64_t b, int sc) {
  asm volatile("{ .reg .pred p; setp.ne.b32 p, %37, 0;\n"
    "wgmma.mma_async.sync.aligned.m64n128k16.f16.f16.f16 {%0, %1, %2, %3, %4, %5, %6, %7, %8, %9, %10, %11, %12, %13, %14, %15, %16, %17, %18, %19, %20, %21, %22, %23, %24, %25, %26, %27, %28, %29, %30, %31}, {%32, %33, %34, %35}, %36, p, 1, 1, 0; }"
    : "+r"(d[0]), "+r"(d[1]), "+r"(d[2]), "+r"(d[3]), "+r"(d[4]), "+r"(d[5]), "+r"(d[6]), "+r"(d[7]),
      "+r"(d[8]), "+r"(d[9]), "+r"(d[10]), "+r"(d[11]), "+r"(d[12]), "+r"(d[13]), "+r"(d[14]), "+r"(d[15]),
      "+r"(d[16]), "+r"(d[17]), "+r"(d[18]), "+r"(d[19]), "+r"(d[20]), "+r"(d[21]), "+r"(d[22]), "+r"(d[23]),
      "+r"(d[24]), "+r"(d[25]), "+r"(d[26]), "+r"(d[27]), "+r"(d[28]), "+r"(d[29]), "+r"(d[30]), "+r"(d[31])
    : "r"(a[0]), "r"(a[1]), "r"(a[2]), "r"(a[3]), "l"(b), "r"(sc));
}
__device__ __forceinline__ void wg_pv_bf16(float (&d)[12], const uint32_t (&a)[4], uint64_t b, int sc) {
  asm volatile("{ .reg .pred p; setp.ne.b32 p, %17, 0;\n"
    "wgmma.mma_async.sync.aligned.m64n24k16.f32.bf16.bf16 {%0, %1, %2, %3, %4, %5, %6, %7, %8, %9, %10, %11}, {%12, %13, %14, %15}, %16, p, 1, 1, 1; }"
    : "+f"(d[0]), "+f"(d[1]), "+f"(d[2]), "+f"(d[3]), "+f"(d[4]), "+f"(d[5]), "+f"(d[6]), "+f"(d[7]),
      "+f"(d[8]), "+f"(d[9]), "+f"(d[10]), "+f"(d[11])
    : "r"(a[0]), "r"(a[1]), "r"(a[2]), "r"(a[3]), "l"(b), "r"(sc));
}
__device__ __forceinline__ void wg_pv_f16(float (&d)[12], const uint32_t (&a)[4], uint64_t b, int sc) {
  asm volatile("{ .reg .pred p; setp.ne.b32 p, %17, 0;\n"
    "wgmma.mma_async.sync.aligned.m64n24k16.f32.f16.f16 {%0, %1, %2, %3, %4, %5, %6, %7, %8, %9, %10, %11}, {%12, %13, %14, %15}, %16, p, 1, 1, 1; }"
    : "+f"(d[0]), "+f"(d[1]), "+f"(d[2]), "+f"(d[3]), "+f"(d[4]), "+f"(d[5]), "+f"(d[6]), "+f"(d[7]),
      "+f"(d[8]), "+f"(d[9]), "+f"(d[10]), "+f"(d[11])
    : "r"(a[0]), "r"(a[1]), "r"(a[2]), "r"(a[3]), "l"(b), "r"(sc));
}

__device__ __forceinline__ void wg_fence() { asm volatile("wgmma.fence.sync.aligned;" ::: "memory"); }
__device__ __forceinline__ void wg_commit() { asm volatile("wgmma.commit_group.sync.aligned;" ::: "memory"); }
template <int N> __device__ __forceinline__ void wg_wait() { asm volatile("wgmma.wait_group.sync.aligned %0;" ::"n"(N) : "memory"); }
template <int N> __device__ __forceinline__ void pin(float (&d)[N]) {
#pragma unroll
  for (int i = 0; i < N; i++) asm volatile("" : "+f"(d[i])::"memory");
}
template <int N> __device__ __forceinline__ void pin(uint32_t (&d)[N]) {
#pragma unroll
  for (int i = 0; i < N; i++) asm volatile("" : "+r"(d[i])::"memory");
}
__device__ __forceinline__ uint64_t dsc(uint32_t lo, uint32_t hi) { uint64_t r; asm("mov.b64 %0, {%1,%2};" : "=l"(r) : "r"(lo), "r"(hi)); return r; }
__device__ __forceinline__ void mbar_init(uint32_t a, int c) { asm volatile("mbarrier.init.shared::cta.b64 [%0], %1;" ::"r"(a), "r"(c) : "memory"); }
__device__ __forceinline__ void map_prefetch(const CUtensorMap* m) { asm volatile("prefetch.tensormap [%0];" ::"l"(m) : "memory"); }
__device__ __forceinline__ void fence_async_smem() { asm volatile("fence.proxy.async.shared::cta;" ::: "memory"); }
__device__ __forceinline__ void bar_sync(int id, int n) { asm volatile("bar.sync %0, %1;" ::"r"(id), "r"(n) : "memory"); }
__device__ __forceinline__ void bar_arrive(int id, int n) { asm volatile("bar.arrive %0, %1;" ::"r"(id), "r"(n) : "memory"); }
__device__ __forceinline__ float bf_lo(uint32_t w) { return __uint_as_float(w << 16); }
__device__ __forceinline__ float bf_hi(uint32_t w) { return __uint_as_float(w & 0xffff0000u); }
__device__ __forceinline__ uint32_t pk_bf(float lo, float hi) { uint32_t r; asm("cvt.rn.bf16x2.f32 %0, %1, %2;" : "=r"(r) : "f"(hi), "f"(lo)); return r; }
__device__ __forceinline__ uint32_t pk_h(float lo, float hi) { uint32_t r; asm("cvt.rn.f16x2.f32 %0, %1, %2;" : "=r"(r) : "f"(hi), "f"(lo)); return r; }
__device__ __forceinline__ uint32_t movm(uint32_t a) { uint32_t d; asm volatile("movmatrix.sync.aligned.m8n8.trans.b16 %0, %1;" : "=r"(d) : "r"(a)); return d; }
__device__ __forceinline__ void ldsm4(uint32_t (&r)[4], uint32_t a) { asm volatile("ldmatrix.sync.aligned.m8n8.x4.shared.b16 {%0,%1,%2,%3}, [%4];" : "=r"(r[0]), "=r"(r[1]), "=r"(r[2]), "=r"(r[3]) : "r"(a) : "memory"); }
__device__ __forceinline__ void ldsm4t(uint32_t (&r)[4], uint32_t a) { asm volatile("ldmatrix.sync.aligned.m8n8.x4.trans.shared.b16 {%0,%1,%2,%3}, [%4];" : "=r"(r[0]), "=r"(r[1]), "=r"(r[2]), "=r"(r[3]) : "r"(a) : "memory"); }
__device__ __forceinline__ void ldsm2t(uint32_t (&r)[2], uint32_t a) { asm volatile("ldmatrix.sync.aligned.m8n8.x2.trans.shared.b16 {%0,%1}, [%2];" : "=r"(r[0]), "=r"(r[1]) : "r"(a) : "memory"); }
__device__ __forceinline__ void mma16(float (&d)[4], const uint32_t (&a)[4], uint32_t b0, uint32_t b1) {
  asm volatile("mma.sync.aligned.m16n8k16.row.col.f32.bf16.bf16.f32 {%0,%1,%2,%3}, {%4,%5,%6,%7}, {%8,%9}, {%0,%1,%2,%3};"
               : "+f"(d[0]), "+f"(d[1]), "+f"(d[2]), "+f"(d[3]) : "r"(a[0]), "r"(a[1]), "r"(a[2]), "r"(a[3]), "r"(b0), "r"(b1));
}
__device__ __forceinline__ void mma8(float (&d)[4], const uint32_t (&a)[2], uint32_t b0) {
  asm volatile("mma.sync.aligned.m16n8k8.row.col.f32.bf16.bf16.f32 {%0,%1,%2,%3}, {%4,%5}, {%6}, {%0,%1,%2,%3};"
               : "+f"(d[0]), "+f"(d[1]), "+f"(d[2]), "+f"(d[3]) : "r"(a[0]), "r"(a[1]), "r"(b0));
}

__device__ __forceinline__ void pdl_trigger() { asm volatile("griddepcontrol.launch_dependents;" ::: "memory"); }
__device__ __forceinline__ void pdl_wait() { asm volatile("griddepcontrol.wait;" ::: "memory"); }
__device__ __forceinline__ void ldg4(uint32_t (&r)[4], const uint4* p) {
  asm volatile("{.reg .b128 t; ld.relaxed.gpu.global.b128 t, [%4]; mov.b128 {%0,%1,%2,%3}, t;}" : "=r"(r[0]), "=r"(r[1]), "=r"(r[2]), "=r"(r[3]) : "l"(p) : "memory");
}
__device__ __forceinline__ void stg4(uint4* p, uint32_t a, uint32_t b, uint32_t c, uint32_t d) {
  asm volatile("{.reg .b128 t; mov.b128 t, {%1,%2,%3,%4}; st.relaxed.gpu.global.b128 [%0], t;}" ::"l"(p), "r"(a), "r"(b), "r"(c), "r"(d) : "memory");
}
__device__ __forceinline__ void stg2(uint2* p, uint32_t a, uint32_t b) {
  asm volatile("{.reg .b64 t; mov.b64 t, {%1,%2}; st.relaxed.gpu.global.b64 [%0], t;}" ::"l"(p), "r"(a), "r"(b) : "memory");
}
__device__ __forceinline__ uint32_t nz(uint32_t w) { return max(w, 1u); }

__device__ __forceinline__ void mbar_wait_u(uint32_t a, uint32_t ph) {
  uint32_t ok;
#pragma unroll 1
  do {
    asm volatile("{.reg .pred p; mbarrier.try_wait.parity.shared::cta.b64 p, [%1], %2; vote.sync.all.pred p, p, 0xffffffff; selp.u32 %0,1,0,p;}" : "=r"(ok) : "r"(a), "r"(ph) : "memory");
  } while (!ok);
}
__device__ __forceinline__ void mbar_arrive_e(uint32_t a) { asm volatile("{.reg .pred p; elect.sync _|p, 0xffffffff; @p mbarrier.arrive.shared::cta.b64 _, [%0];}" ::"r"(a) : "memory"); }
__device__ __forceinline__ void tma2_e(uint32_t d, const CUtensorMap* m, int c0, int c1, uint32_t mb) {
  asm volatile("{.reg .pred p; elect.sync _|p, 0xffffffff; @p cp.async.bulk.tensor.2d.shared::cluster.global.mbarrier::complete_tx::bytes [%0], [%1, {%3,%4}], [%2];}" ::"r"(d), "l"(m), "r"(mb), "r"(c0), "r"(c1) : "memory");
}
__device__ __forceinline__ void tma4_e(uint32_t d, const CUtensorMap* m, int c0, int c1, int c2, int c3, uint32_t mb) {
  asm volatile("{.reg .pred p; elect.sync _|p, 0xffffffff; @p cp.async.bulk.tensor.4d.shared::cluster.global.mbarrier::complete_tx::bytes [%0], [%1, {%3,%4,%5,%6}], [%2];}" ::"r"(d), "l"(m), "r"(mb), "r"(c0), "r"(c1), "r"(c2), "r"(c3) : "memory");
}
__device__ __forceinline__ void l2_prefetch_e(const void* p, uint32_t n) { asm volatile("{.reg .pred p; elect.sync _|p, 0xffffffff; @p cp.async.bulk.prefetch.L2.global [%0], %1;}" ::"l"(p), "r"(n) : "memory"); }
__device__ __forceinline__ void cnt_arrive_e(unsigned* c) { asm volatile("{.reg .pred p; elect.sync _|p, 0xffffffff; @p red.release.gpu.global.add.u32 [%0], 1;}" ::"l"(c) : "memory"); }
__device__ __forceinline__ void cnt_arrive_relaxed_e(unsigned* c) { asm volatile("{.reg .pred p; elect.sync _|p, 0xffffffff; @p red.relaxed.gpu.global.add.u32 [%0], 1;}" ::"l"(c) : "memory"); }
__device__ __forceinline__ void cnt_wait_u(const unsigned* c, unsigned target) {
  int it = 0;
#pragma unroll 1
  while (true) {
    unsigned v;
    asm volatile("ld.relaxed.gpu.global.u32 %0, [%1];" : "=r"(v) : "l"(c) : "memory");
    if (__all_sync(0xffffffffu, v >= target)) break;
    if (++it > (1 << 22)) break;
  }
}

__device__ __forceinline__ void mbar_expect_e(uint32_t a, uint32_t b) { asm volatile("{.reg .pred p; elect.sync _|p, 0xffffffff; @p mbarrier.arrive.expect_tx.shared::cta.b64 _, [%0], %1;}" ::"r"(a), "r"(b) : "memory"); }
__device__ __forceinline__ void bulk_ne(uint32_t d, const void* s, uint32_t n, uint32_t m) {
  asm volatile("{.reg .pred p; elect.sync _|p, 0xffffffff; @p cp.async.bulk.shared::cluster.global.mbarrier::complete_tx::bytes [%0], [%1], %2, [%3];}" ::"r"(d), "l"(s), "r"(n), "r"(m) : "memory");
}
__device__ __forceinline__ void bulk_store_e(void* g, uint32_t s, uint32_t n) {
  asm volatile("{.reg .pred p; elect.sync _|p, 0xffffffff; @p cp.async.bulk.global.shared::cta.bulk_group [%0], [%1], %2; @p cp.async.bulk.commit_group;}" ::"l"(g), "r"(s), "r"(n) : "memory");
}
__device__ __forceinline__ void tma2_store_e(const CUtensorMap* m, int c0, int c1, uint32_t s) {
  asm volatile("{.reg .pred p; elect.sync _|p, 0xffffffff; @p cp.async.bulk.tensor.2d.global.shared::cta.bulk_group [%0, {%2,%3}], [%1]; @p cp.async.bulk.commit_group;}" ::"l"(m), "r"(s), "r"(c0), "r"(c1) : "memory");
}
__device__ __forceinline__ void bulk_wait_all() { asm volatile("cp.async.bulk.wait_group 0;" ::: "memory"); }
__device__ __forceinline__ void bulk_wait_read() { asm volatile("cp.async.bulk.wait_group.read 0;" ::: "memory"); }
__device__ __forceinline__ void stsm4t(uint32_t a, uint32_t r0, uint32_t r1, uint32_t r2, uint32_t r3) {
  asm volatile("stmatrix.sync.aligned.m8n8.x4.trans.shared.b16 [%0], {%1,%2,%3,%4};" ::"r"(a), "r"(r0), "r"(r1), "r"(r2), "r"(r3) : "memory");
}

__device__ __forceinline__ bool elect1() { uint32_t p; asm volatile("{.reg .pred p; elect.sync _|p, 0xffffffff; selp.u32 %0,1,0,p;}" : "=r"(p)); return p; }
__device__ __forceinline__ void mbar_expect(uint32_t a, uint32_t b) { asm volatile("mbarrier.arrive.expect_tx.shared::cta.b64 _, [%0], %1;" ::"r"(a), "r"(b) : "memory"); }

__device__ __forceinline__ float rsq(float x) { float y; asm("rsqrt.approx.ftz.f32 %0, %1;" : "=f"(y) : "f"(x)); return y; }
__device__ __forceinline__ float sqr(float x) { float y; asm("sqrt.approx.ftz.f32 %0, %1;" : "=f"(y) : "f"(x)); return y; }
__device__ __forceinline__ float rcp(float x) { float y; asm("rcp.approx.ftz.f32 %0, %1;" : "=f"(y) : "f"(x)); return y; }
__device__ __forceinline__ float sigm(float x) { float e; asm("ex2.approx.ftz.f32 %0, %1;" : "=f"(e) : "f"(x * -1.4426950408889634f)); return rcp(1.f + e); }
template <class T> __device__ __forceinline__ void keep(T& v) { asm volatile("" : "+r"(v)); }
template <class T> __device__ __forceinline__ void keepp(T*& v) { asm volatile("" : "+l"(v)); }

__device__ __forceinline__ uint32_t lds32(uint32_t a) { uint32_t v; asm volatile("ld.shared.u32 %0, [%1];" : "=r"(v) : "r"(a)); return v; }
__device__ __forceinline__ float2 lds64f(uint32_t a) { float2 v; asm volatile("ld.shared.v2.f32 {%0,%1}, [%2];" : "=f"(v.x), "=f"(v.y) : "r"(a)); return v; }
__device__ __forceinline__ float4 lds128f(uint32_t a) { float4 v; asm volatile("ld.shared.v4.f32 {%0,%1,%2,%3}, [%4];" : "=f"(v.x), "=f"(v.y), "=f"(v.z), "=f"(v.w) : "r"(a)); return v; }
__device__ __forceinline__ uint4 lds128(uint32_t a) { uint4 v; asm volatile("ld.shared.v4.u32 {%0,%1,%2,%3}, [%4];" : "=r"(v.x), "=r"(v.y), "=r"(v.z), "=r"(v.w) : "r"(a)); return v; }
__device__ __forceinline__ void sts32(uint32_t a, uint32_t v) { asm volatile("st.shared.u32 [%0], %1;" ::"r"(a), "r"(v)); }
__device__ __forceinline__ void sts32f(uint32_t a, float v) { asm volatile("st.shared.f32 [%0], %1;" ::"r"(a), "f"(v)); }
__device__ __forceinline__ void sts64f(uint32_t a, float x, float y) { asm volatile("st.shared.v2.f32 [%0], {%1,%2};" ::"r"(a), "f"(x), "f"(y)); }
__device__ __forceinline__ void sts128(uint32_t a, uint32_t x, uint32_t y, uint32_t z, uint32_t w) { asm volatile("st.shared.v4.u32 [%0], {%1,%2,%3,%4};" ::"r"(a), "r"(x), "r"(y), "r"(z), "r"(w)); }
__device__ __forceinline__ void sts128f(uint32_t a, float x, float y, float z, float w) { asm volatile("st.shared.v4.f32 [%0], {%1,%2,%3,%4};" ::"r"(a), "f"(x), "f"(y), "f"(z), "f"(w)); }
__device__ __forceinline__ void stsm2t(uint32_t a, uint32_t r0, uint32_t r1) { asm volatile("stmatrix.sync.aligned.m8n8.x2.trans.shared.b16 [%0], {%1,%2};" ::"r"(a), "r"(r0), "r"(r1) : "memory"); }
__device__ __forceinline__ uint32_t smem_base() {
  extern __shared__ __align__(1024) uint8_t sm_[];
  return __shfl_sync(0xffffffffu, (uint32_t)__cvta_generic_to_shared(sm_), 0);
}

__device__ __forceinline__ void bar_sync_after(int id, int n, uint32_t v, uint32_t zero) { bar_sync((v & zero) | id, n); }

constexpr float QSCALE = 0.23570226039551584f * 1.4426950408889634f;
constexpr uint32_t H_CA = 0x2cb7u, H_CB = 0x5a9eu;
constexpr float L_MIN = 4.0f;
#define MUMASK 0xc0
#define ORD 0
#define LV 5
#define SPLIT 0
constexpr uint32_t MU = MUMASK;

template <int W>
__device__ __forceinline__ void q_epilogue(const float (&d)[48], uint32_t sa, int warp, int lane) {
  const uint32_t st = sa + SM1_MISC + 128 + W * 704 + (lane & 3) * 16;
  const float cs0 = d[W ? 44 : 0], cs1 = d[W ? 46 : 2];
  const uint32_t a = sa + SM_W + (W * 88 + (lane >> 4) * 8 + (lane & 7)) * 128 + (((warp * 2 + ((lane >> 3) & 1)) ^ (lane & 7)) << 4);
  uint32_t v[22];
#pragma unroll
  for (int i = 0; i < 11; i++) {
    const float4 s2 = lds128f(st + i * 64);
    const int b = (W ? i : i + 1) * 4;
    v[2 * i] = pk_h((d[b] - s2.x * cs0) * s2.y, (d[b + 1] - s2.z * cs0) * s2.w);
    v[2 * i + 1] = pk_h((d[b + 2] - s2.x * cs1) * s2.y, (d[b + 3] - s2.z * cs1) * s2.w);
  }
#pragma unroll
  for (int i = 0; i < 10; i += 2) stsm4t(a + i * 1024, v[2 * i], v[2 * i + 1], v[2 * i + 2], v[2 * i + 3]);
  stsm2t(a + 10240, v[20], v[21]);
}

__global__ void __launch_bounds__(NTHR, 1)
pre_kernel(Scratch* __restrict__ G, const __nv_bfloat16* __restrict__ wk, const __nv_bfloat16* __restrict__ wv,
           const __grid_constant__ CUtensorMap m_x, const __grid_constant__ CUtensorMap m_wq) {
  const uint32_t sa = smem_base(), mb = sa + SM1_MISC;
  const int b = blockIdx.x, grp = b / 11, role = b - grp * 11;
  const int gtok = min(grp * 176, S_ - 176);
  const bool prod = __all_sync(0xffffffffu, threadIdx.x < 32), qr = role >= 2;
  const int ptok = gtok + (qr ? 0 : role * 88);
  if (prod && elect1()) {
    mbar_init(mb, 1);
    asm volatile("fence.mbarrier_init.release.cluster;" ::: "memory");
    asm volatile("cp.async.bulk.tensor.2d.shared::cluster.global.mbarrier::complete_tx::bytes [%0], [%1, {0,%3}], [%2];" ::"r"(sa + SM_X + (qr ? 1024 : 0)), "l"(&m_x), "r"(mb), "r"(ptok) : "memory");
    if (qr) asm volatile("cp.async.bulk.tensor.2d.shared::cluster.global.mbarrier::complete_tx::bytes [%0], [%1, {%3,0}], [%2];" ::"r"(sa + SM_W), "l"(&m_wq), "r"(mb), "r"((role - 2) * 64) : "memory");
  }
  if (prod) {
    if (elect1()) {
#pragma unroll
      for (int i = 1; i < 12; i++) mbar_init(mb + 8 * i, i < 9 ? 1 : 8);
      asm volatile("fence.mbarrier_init.release.cluster;" ::: "memory");
    }
#pragma unroll 1
    for (int i = 0; i < 9; i++) {
      if (qr && i >= 6) mbar_wait_u(mb + 24 + 8 * i, 0);
      const uint32_t dst = sa + SM_X + (qr ? 1024 + (i >= 6 ? i - 6 : i) * XSLOT : i * KSLOT);
      if (i) tma2_e(dst, &m_x, i * 64, ptok, mb + 8 * i);
      if (qr) {
        if (i) tma2_e(sa + SM_W + i * 8192, &m_wq, (role - 2) * 64, i * 64, mb + 8 * i);
        tma2_e(dst + 11264, &m_x, i * 64, ptok + 88, mb + 8 * i);
      }
      mbar_expect_e(mb + 8 * i, qr ? 30720 : 11264);
      if (i == 0) bar_arrive(2, qr ? 288 : 512);
    }
    return;
  }
  const int lane = threadIdx.x & 31;
  const int wid = (__shfl_sync(0xffffffffu, threadIdx.x >> 5, 0) + 12) & 15, wg = wid >> 2, warp = wid & 3, tid = wid * 32 + lane;
  PROF_T(0, 128); PROF_C(1, 128);
  const uint64_t da = dsc(((sa + SM_W) >> 4) | (1u << 16), 64u | (1u << 30));
  if (role >= 2) {
    const int slice = role - 2;
    if (wid > 12) {
      const int i = tid - 416, tok = gtok + i * 2;
      if (i < 88) {
        float4 v;
        {
          int it = 0;
#pragma unroll 1
          while (true) {
            unsigned long long lo, hi;
            asm volatile("ld.relaxed.gpu.global.v2.b64 {%0,%1}, [%2];" : "=l"(lo), "=l"(hi) : "l"(&G->st0[tok]) : "memory");
            v = make_float4(__uint_as_float((uint32_t)lo), __uint_as_float((uint32_t)(lo >> 32)), __uint_as_float((uint32_t)hi), __uint_as_float((uint32_t)(hi >> 32)));
            if (__float_as_uint(v.y) != 0u && __float_as_uint(v.w) != 0u) break;
            if (++it > (1 << 22)) break;
            __nanosleep(60);
          }
        }
        sts128f(mb + 128 + i * 16, v.x, v.y * (QSCALE / 512.f), v.z, v.w * (QSCALE / 512.f));
      }
      __syncwarp();
      PROF_C(42, 416);
      bar_arrive(1, 352);
    } else if (wg < 2) {
      if (wid < 7) {
#pragma unroll
        for (int i = 0; i < 2; i++) sts128(sa + SM_X + wid * XSLOT + i * 512 + lane * 16, 0x3f803f80u, 0x3f803f80u, 0x3f803f80u, 0x3f803f80u);
      }
      fence_async_smem();
      float d[48];
#pragma unroll
      for (int i = 0; i < 48; i++) d[i] = 0.f;
      pin(d);
      const uint64_t db = dsc(((sa + SM_X + wg * 12288) >> 4) | (1u << 16), 64u | (1u << 30));
      bar_sync(2, 288);
      PROF_C(2, 128);
#pragma unroll
      for (int kt = 0; kt < 9; kt++) {
        mbar_wait_u(mb + 8 * kt, 0);
        if (kt == 0) PROF_C(3, 128);
        wg_fence();
#pragma unroll
        for (int ks = 0; ks < 4; ks++) wg_ss_n96_tA(d, da + (kt * 512 + ks * 128), db + ((kt % 6) * (XSLOT / 16) + ks * 2), 1);
        wg_commit();
        if (kt >= 1 && kt <= 3) { wg_wait<1>(); mbar_arrive_e(mb + 64 + 8 * kt); }
      }
      uint4* dst = G->q + (slice * S_ + gtok + wg * 88) * 8;
      wg_wait<0>(); pin(d);
      PROF_C(4, 128);
      pdl_trigger();
      bar_sync(1, 352);
      PROF_C(5, 128);
      if (wg == 0) q_epilogue<0>(d, sa, warp, lane); else q_epilogue<1>(d, sa, warp, lane);
      PROF_C(46, 128);
      fence_async_smem();
      bar_sync(4 + wg, 128);
      if (warp == 0) {
        bulk_store_e(dst, sa + SM_W + wg * 11264, 11264);
        bulk_wait_read();
      }
    } else {
      const int i = (grp * 9 + slice) * 128 + (tid & 127);
      if (i < S_) G->st2[i] = make_float4(0.f, 0.f, 0.f, 0.f);
      else if (i < S_ + 33) G->cnt[(i - S_) * 32] = 0u;

    }
  } else {
    const int tok0 = gtok + role * 88;
    uint4 gw[6];
    const int w15 = wid - (wid > 12), t15 = w15 * 32 + lane;
    if (t15 < 432) {
#pragma unroll
      for (int i = 0; i < 6; i++) gw[i] = __ldg(reinterpret_cast<const uint4*>(i < 3 ? wk : wv) + (i % 3) * 432 + t15);
    }
    if (wid < 9) {
#pragma unroll
      for (int i = 0; i < 2; i++) sts128(sa + SM_X + wid * KSLOT + 11264 + i * 512 + lane * 16, 0x3f803f80u, 0x3f803f80u, 0x3f803f80u, 0x3f803f80u);
    }
    if (t15 < 432) {
      const int q4 = t15 / 9, u = (t15 - q4 * 9) * 4;
#pragma unroll
      for (int j = 0; j < 4; j++) {
        const int kr = ((u + j) * 57) >> 9, w = u + j - kr * 9, k = q4 * 4 + kr;
        const uint32_t pk = sa + SM_W + k * 128 + ((w * 4) ^ ((k & 7) << 4)), pv = sa + SM_W + k * 128 + ((w * 4 + 40) ^ ((k & 7) << 4));
#pragma unroll
        for (int i = 0; i < 6; i++) sts32((i < 3 ? pk : pv) + (i % 3) * 24576, reinterpret_cast<const uint32_t*>(&gw[i])[j]);
      }
    }
    fence_async_smem();
    bar_sync(2, 512);
    PROF_C(32, 0);
    if (wg == 0) {
      float d[48];
#pragma unroll
      for (int i = 0; i < 48; i++) d[i] = 0.f;
      pin(d);
      const uint64_t db = dsc(((sa + SM_X) >> 4) | (1u << 16), 64u | (1u << 30));
      bar_sync(1, 480);
      wg_fence();
#pragma unroll
      for (int kt = 0; kt < 9; kt++) {
#pragma unroll
        for (int ks = 0; ks < 4; ks++) wg_ss_n96_tA(d, da + (kt * 512 + ks * 128), db + (kt * (KSLOT / 16) + ks * 2), 1);
      }
      wg_commit();
      wg_wait<0>(); pin(d);
      PROF_C(33, 0);
      if (warp < 3) {
        const uint32_t p = sa + SM_W + (2 * (lane & 3)) * 176 + (warp * 16 + (lane >> 2)) * 4;
#pragma unroll
        for (int i = 0; i < 11; i++) {
          const float4 s2 = lds128f(mb + 128 + (lane & 3) * 16 + i * 64);
          sts32f(p + i * 1408, (d[4 * i] - s2.x * d[44]) * s2.y);  sts32f(p + i * 1408 + 176, (d[4 * i + 1] - s2.z * d[44]) * s2.w);
          if (warp < 2) { sts32f(p + i * 1408 + 32, (d[4 * i + 2] - s2.x * d[46]) * s2.y);  sts32f(p + i * 1408 + 208, (d[4 * i + 3] - s2.z * d[46]) * s2.w); }
        }
      }
    } else {
      float dd[4][4] = {};
      const uint32_t p = sa + SM_X + ((w15 - 4) * 8 + (lane & 7)) * 128 + (((lane >> 3) ^ (lane & 7)) << 4);
#pragma unroll
      for (int kt = 0; kt < 9; kt++) {
        mbar_wait_u(mb + 8 * kt, 0);
#pragma unroll
        for (int j = 0; j < 2; j++) {
          uint32_t f[4];
          ldsm4(f, (p ^ (j * 64)) + kt * KSLOT);
          const uint32_t a0[4] = {f[0], 0x3f803f80u, f[1], 0x3f803f80u}, a1[4] = {f[2], 0x3f803f80u, f[3], 0x3f803f80u};
          mma16(dd[2 * j], a0, f[0], f[1]);
          mma16(dd[2 * j + 1], a1, f[2], f[3]);
        }
      }
      float d0[4], d1[4];
#pragma unroll
      for (int i = 0; i < 4; i++) { d0[i] = dd[0][i] + dd[1][i]; d1[i] = dd[2][i] + dd[3][i]; }
      const int r = lane >> 2;
      if ((r >> 1) == (lane & 3)) {
        const float m = ((r & 1) ? d0[3] + d1[3] : d0[2] + d1[2]) * (1.f / D_), q = ((r & 1) ? d0[1] + d1[1] : d0[0] + d1[0]) * (1.f / D_);
        const float rs = rsq(fmaxf(q - m * m, 0.f) + 1e-5f);
        const int tl = (w15 - 4) * 8 + r;
          asm volatile("st.relaxed.gpu.global.b64 [%0], %1;" ::"l"(&G->st0[tok0 + tl]),
                       "l"((unsigned long long)__float_as_uint(m) | ((unsigned long long)max(__float_as_uint(rs), 1u) << 32)) : "memory");
        sts64f(mb + 128 + tl * 8, m, rs);
      }
      __syncwarp();
      PROF_C(41, 128);
      bar_arrive(1, 480);
    }
    bar_sync(3, 480);
    PROF_C(34, 0);
    pdl_trigger();
    const int jw = wg == 3 ? warp - 1 : warp, tl = jw * 32 + lane, tok = tok0 + tl;
    if (jw < 3) {
      const bool on = tl < 88;
      const uint32_t p = sa + SM_W + min(tl, 87) * 176;
      const bool mu = (MU >> ((tok >> 4) & 7)) & 1;
      const int o = (tok >> 3) * 40 + (tok & 7);
      float res = 0.f;
      if (wg == 0) {
        const float ks = mu ? 512.f : -1.f / 512.f;
        const float4 a = lds128f(p), c = lds128f(p + 16), e = lds128f(p + 32), f = lds128f(p + 48);
        const float2 t = lds64f(p + 64), u = lds64f(p + 144);
        if (on) {
          G->kv[o] = make_uint4(pk_h(a.x * ks, a.y * ks), pk_h(a.z * ks, a.w * ks), pk_h(c.x * ks, c.y * ks), pk_h(c.z * ks, c.w * ks));
          G->kv[o + 8] = make_uint4(pk_h(e.x * ks, e.y * ks), pk_h(e.z * ks, e.w * ks), pk_h(f.x * ks, f.y * ks), pk_h(f.z * ks, f.w * ks));
          G->kv[o + 16] = make_uint4(pk_h(t.x * ks, t.y * ks), mu ? (0xe000u | (H_CB << 16)) : 0x1800u, mu ? pk_h(u.x, u.y) : pk_bf(u.x, u.y), mu ? 0x3c00u : 0x3f80u);
          res = a.x * a.x + a.y * a.y + a.z * a.z + a.w * a.w + c.x * c.x + c.y * c.y + c.z * c.z + c.w * c.w + e.x * e.x + e.y * e.y +
                e.z * e.z + e.w * e.w + f.x * f.x + f.y * f.y + f.z * f.z + f.w * f.w + t.x * t.x + t.y * t.y;
          if (!(res <= 14400.f)) res = INFINITY;
        }
      } else if (wg == 1) {
        const float4 a = lds128f(p + 80), c = lds128f(p + 96), e = lds128f(p + 112), f = lds128f(p + 128);
        if (on) {
          G->kv[o + 24] = mu ? make_uint4(pk_h(a.x, a.y), pk_h(a.z, a.w), pk_h(c.x, c.y), pk_h(c.z, c.w)) : make_uint4(pk_bf(a.x, a.y), pk_bf(a.z, a.w), pk_bf(c.x, c.y), pk_bf(c.z, c.w));
          G->kv[o + 32] = mu ? make_uint4(pk_h(e.x, e.y), pk_h(e.z, e.w), pk_h(f.x, f.y), pk_h(f.z, f.w)) : make_uint4(pk_bf(e.x, e.y), pk_bf(e.z, e.w), pk_bf(f.x, f.y), pk_bf(f.z, f.w));
        }
      } else if (wg == 3) {
        const float4 a = lds128f(p + 80), c = lds128f(p + 96), e = lds128f(p + 112), f = lds128f(p + 128);
        const float2 u = lds64f(p + 144);
        const float v[18] = {a.x, a.y, a.z, a.w, c.x, c.y, c.z, c.w, e.x, e.y, e.z, e.w, f.x, f.y, f.z, f.w, u.x, u.y};
        bool ok = true;
#pragma unroll
        for (int i = 0; i < 18; i++) ok = ok & (fabsf(v[i]) <= 30000.f) & (bool)__any_sync(0xffffffffu, fabsf(v[i]) >= 0.0078125f);
        if (!ok) res = INFINITY;
      } else {
#pragma unroll
        for (int i = 0; i < 5; i++) {
          const float4 a = lds128f(p + 32 * i), c = lds128f(p + 32 * i + 16);
          if (on) G->kvb[o + 8 * i] = make_uint4(pk_bf(a.x, a.y), pk_bf(a.z, a.w), pk_bf(c.x, c.y), pk_bf(c.z, c.w));
        }
      }
      const uint32_t m = __reduce_max_sync(0xffffffffu, __float_as_uint(res));
      if (lane == 0 && (wg == 0 || wg == 3)) G->rsq[(grp * 2 + role) * 6 + wg + jw] = __uint_as_float(m);
    }
    PROF_C(35, 0);
  }
  PROF_C(6, 128); PROF_T(7, 128);
}

template <int G0, int G1>
__device__ __forceinline__ void exp_tile(const uint32_t (&s)[32], uint32_t (&p)[8][4], uint32_t m2, uint32_t half) {
#pragma unroll
  for (int j = 0; j < (G1 - G0) * 4; j++) {
    const int jj = ORD >= 3 ? (G1 - G0) * 4 - 1 - j : j, od = ORD % 3;
    const int g = G0 + (od == 0 ? jj >> 2 : od == 1 ? jj % (G1 - G0) : (jj >> 1) % (G1 - G0));
    const int i = od == 0 ? jj & 3 : od == 1 ? jj / (G1 - G0) : (jj & 1) + 2 * (jj / (2 * (G1 - G0)));
    uint32_t y = s[g * 4 + i], r;
    if ((MU >> g) & 1) {
      asm("ex2.approx.f16x2 %0, %1;" : "=r"(r) : "r"(y));
    } else {
      uint32_t z, m, e;
      asm("mad.lo.u32 %0, %1, %2, 0x47014701;" : "=r"(z) : "r"(y), "r"(m2));
      asm("lop3.b32 %0, %1, 0x007f007f, %2, 0xEA;" : "=r"(m) : "r"(z), "r"(half));
      asm("and.b32 %0, %1, 0xff81ff81;" : "=r"(e) : "r"(z));
      asm("fma.rn.bf16x2 %0, %1, %2, %3;" : "=r"(r) : "r"(z), "r"(m), "r"(e));
    }
    p[g][i] = r;
  }
}
template <int G0, int G1>
__device__ __forceinline__ void pv_tile(float (&o)[12], const uint32_t (&p)[8][4], uint64_t dv) {
#pragma unroll
  for (int g = G0; g < G1; g++) {
    if ((MU >> g) & 1) wg_pv_f16(o, p[g], dv + g * 80, 1);
    else wg_pv_bf16(o, p[g], dv + g * 80, 1);
  }
}
__device__ __forceinline__ void exp_pv(const uint32_t (&s)[32], float (&o)[12], uint64_t dv, uint32_t m2, uint32_t half) {
  uint32_t p[8][4];
  exp_tile<SPLIT, 8>(s, p, m2, half); wg_fence(); pv_tile<SPLIT, 8>(o, p, dv);
}

__device__ __noinline__ void exact_tile(Scratch* G, const __nv_bfloat16* x, const __nv_bfloat16* wq, int tile, int head) {
  const int t = threadIdx.x & 127, row = t >> 1, tok = tile * 64 + row, hf = t & 1;
  const float2 st = __ldcg(&G->st0[tok]);
  float q[18], o[18];
#pragma unroll
  for (int d = 0; d < 18; d++) { q[d] = 0.f; o[d] = 0.f; }
#pragma unroll 1
  for (int k = hf * 288; k < hf * 288 + 288; k++) {
    const float xn = (__bfloat162float(x[tok * D_ + k]) - st.x) * st.y;
    const uint32_t* w = reinterpret_cast<const uint32_t*>(wq + k * D_ + head * 18);
#pragma unroll
    for (int j = 0; j < 9; j++) { uint32_t v = w[j]; q[2 * j] += xn * bf_lo(v); q[2 * j + 1] += xn * bf_hi(v); }
  }
#pragma unroll
  for (int d = 0; d < 18; d++) q[d] = (q[d] + __shfl_xor_sync(0xffffffffu, q[d], 1)) * QSCALE;
  float m = -INFINITY, l = 0.f;
#pragma unroll 1
  for (int j = hf * 1024; j < hf * 1024 + 1024; j++) {
    uint32_t w[20];
#pragma unroll
    for (int i = 0; i < 5; i++) { const uint4 v = G->kvb[(j >> 3) * 40 + (j & 7) + 8 * i]; w[4 * i] = v.x; w[4 * i + 1] = v.y; w[4 * i + 2] = v.z; w[4 * i + 3] = v.w; }
    float s = 0.f;
#pragma unroll
    for (int d = 0; d < 9; d++) s += q[2 * d] * bf_lo(w[d]) + q[2 * d + 1] * bf_hi(w[d]);
    const float mn = fmaxf(m, s), a = exp2f(m - mn), p = exp2f(s - mn);
    m = mn; l = l * a + p;
#pragma unroll
    for (int d = 0; d < 9; d++) { o[2 * d] = o[2 * d] * a + p * bf_lo(w[10 + d]); o[2 * d + 1] = o[2 * d + 1] * a + p * bf_hi(w[10 + d]); }
  }
  const float m2 = __shfl_xor_sync(0xffffffffu, m, 1), mn = fmaxf(m, m2), a = exp2f(m - mn);
  l *= a; l += __shfl_xor_sync(0xffffffffu, l, 1);
  const float inv = 1.f / l;
#pragma unroll
  for (int d = 0; d < 18; d++) { o[d] *= a; o[d] = (o[d] + __shfl_xor_sync(0xffffffffu, o[d], 1)) * inv; }
  uint32_t* fx = G->fix + (blockIdx.x * 16 + (threadIdx.x >> 5)) * 160;
  const int ln = t & 31, sw = ((ln >> 4) ^ (head >> 4)) & 1;
  if (hf == 0) {
#pragma unroll
    for (int j = 0; j < 8; j++) fx[(((ln >> 1) & 7) * 4 + (j & 3)) * 4 + (j >> 2) * 2 + sw] = pk_bf(o[2 * j], o[2 * j + 1]);
    fx[128 + ((ln >> 1) & 7) * 2 + sw] = pk_bf(o[16], o[17]);
  }
  __syncwarp();
  stg4(G->o + (tile * 36 + head) * 128 + t, nz(fx[ln * 4]), fx[ln * 4 + 1], fx[ln * 4 + 2], fx[ln * 4 + 3]);
  if (ln < 8) stg2(reinterpret_cast<uint2*>(G->o + (tile * 36 + 32 + (head >> 3)) * 128 + (t & 96) + ln * 4 + (head & 3)) + ((head >> 2) & 1), nz(fx[128 + ln * 2]), fx[129 + ln * 2]);
  __syncwarp();
}

__device__ __forceinline__ void q_addr(uint32_t base, int hg, int wg, int warp, int lane, uint32_t (&a)[3]) {
  const int c = lane & 3, r = lane >> 2, p2 = hg * 4 + wg * 9 + 8, p0 = p2 - 8 + c, p1 = p0 + 4;
  const uint32_t qr = base + (warp * 16 + (hg & 4) * 2 + r) * 128;
  a[0] = qr + (p0 >> 5) * 8192 + (((p0 & 31) * 4) ^ (r << 4));
  a[1] = qr + (p1 >> 5) * 8192 + (((p1 & 31) * 4) ^ (r << 4));
  a[2] = (qr + (p2 >> 5) * 8192 + (((p2 & 31) * 4) ^ (r << 4))) ^ ((c & 1) * 1024);
}
__device__ __forceinline__ float key_radius(uint32_t rsq_addr, int lane) {
  const uint4 rv = lds128(rsq_addr + lane * 16);
  const uint32_t rw = lds32(rsq_addr + 512 + (lane & 15) * 4);
  return sqr(__uint_as_float(__reduce_max_sync(0xffffffffu, max(max(max(rv.x, rv.y), max(rv.z, rv.w)), rw)))) * 1.001f + 1e-4f;
}
__device__ __forceinline__ uint32_t load_q(const uint32_t (&a)[3], uint32_t (&q0)[4]) {
  q0[0] = lds32(a[0]); q0[1] = lds32(a[0] ^ 1024); q0[2] = lds32(a[1]); q0[3] = lds32(a[1] ^ 1024);
  return lds32(a[2]);
}
__device__ __forceinline__ bool bound_q(const uint32_t (&q0)[4], uint32_t wt, float rk, int c, uint32_t& qa, uint32_t& qb) {
  const uint32_t w0 = q0[0], w1 = q0[1], w2 = q0[2], w3 = q0[3];
  const float2 u0 = __half22float2(*reinterpret_cast<const __half2*>(&w0)), v0 = __half22float2(*reinterpret_cast<const __half2*>(&w2));
  const float2 u1 = __half22float2(*reinterpret_cast<const __half2*>(&w1)), v1 = __half22float2(*reinterpret_cast<const __half2*>(&w3));
  const float2 e = __half22float2(*reinterpret_cast<const __half2*>(&wt));
  const float t0 = u0.x * u0.x + u0.y * u0.y + v0.x * v0.x + v0.y * v0.y, t1 = u1.x * u1.x + u1.y * u1.y + v1.x * v1.x + v1.y * v1.y;
  float t = ((c & 1) ? t1 : t0) + __shfl_xor_sync(0xffffffffu, (c & 1) ? t0 : t1, 1);
  t += __shfl_xor_sync(0xffffffffu, t, 2);
  const float n = sqr(t + e.x * e.x + e.y * e.y);
  const float m = n * rk + 0.05f / 512.f;
  const uint32_t mh = (uint32_t)__half_as_ushort(__float2half_ru(m)) | (H_CA << 16);
  const uint32_t oth = __shfl_xor_sync(0xffffffffu, (c & 1) ? wt : mh, 1);
  qa = c >= 2 ? 0u : c ? oth : wt;
  qb = c >= 2 ? 0u : c ? mh : oth;
  return !(m <= 60.f / 512.f) || !(n <= 120.f / 512.f);
}

struct Params {
  Scratch* G;
  const __nv_bfloat16 *x, *wq, *wr, *wg, *wu, *wd;
  __nv_bfloat16* out;
};
struct Maps { CUtensorMap wo, wo7, wt, g, u, xt, d, h; };

constexpr int B_END = 1, B_EX = 2  , B_THR = 4, B_O = 5  , B_SEL = 7, B_H = 9  , B_XS = 11, B_PART = 12, B_ACT = 13;

__global__ void __launch_bounds__(640, 1)
main_kernel(const Params P, const __grid_constant__ Maps M) {
  const uint32_t sa = smem_base(), mb = sa + SM_MISC;
  int tid = threadIdx.x, lane = tid & 31, c = lane & 3, r = lane >> 2;
  const int wid = __shfl_sync(0xffffffffu, tid >> 5, 0), wg = wid >> 2, warp = wid & 3;
  const int b = blockIdx.x, tg = b >> 3, hg = b & 7;
  Scratch* const G = P.G;
  const uint32_t qs = (sa + 1024) & ~2047u;
  PROF_T(8, 128); PROF_C(9, 128);
  if (wid == 16 && elect1()) {
#pragma unroll
    for (int i = 0; i < 12; i++) mbar_init(mb + 8 * i, i == 5 ? 2 : i < 8 ? 1 : i < 10 ? 16 : i == 10 ? 21 : 1);
    asm volatile("fence.mbarrier_init.release.cluster;" ::: "memory");
  }
  if (wid == 17) { sts128(mb + MS_K, 0u, 0u, 0xfffffffeu, 0x3f003f00u); sts128(mb + MS_BAD + (lane & 1) * 16, 0u, 0u, 0u, 0u); sts32(mb + MS_ROW + lane * 4, 0u); }
  if (wg == 4) {
    asm volatile("setmaxnreg.dec.sync.aligned.u32 32;");
    const int fc = (b >> 1) * 72 + (b & 1) * 32;
    unsigned* const cnt = &G->cnt[32 + tg * 64];
    {
      const void* src = warp < 2 ? (const void*)(G->q + ((hg + warp) * S_ + tg * 128) * 8) : warp == 2 ? (const void*)G->kv : (const void*)G->rsq;
      const uint32_t dst = warp < 2 ? qs + warp * 8192 : warp == 2 ? sa + SM_KV : mb + MS_RSQ;
      const uint32_t bytes = warp < 2 ? 8192 : warp == 2 ? 10240 : 576, bar = warp >= 2 ? mb + MB_KV : mb + MB_Q;
      bar_sync(14, 128);
      bar_arrive(0, 640);
      pdl_wait();
      bulk_ne(dst, src, bytes, bar);
      PROF_C(10, 512);
    }
    if (warp == 3 && elect1()) {
      mbar_expect(mb + MB_KV, 10816); mbar_expect(mb + MB_Q, 16384); mbar_expect(mb + MB_KV1, 20480); mbar_expect(mb + MB_Q + 8, 16384);
      mbar_expect(mb + MB_KV + 8, 133120); mbar_expect(mb + MB_WO, 82944); mbar_expect(mb + MB_XT, 18432); mbar_expect(mb + MB_GU, 92160);
      mbar_expect(mb + MB_DOWN, 46080);
    }
    if (warp == 2) bulk_ne(sa + SM_KV + 10240, G->kv + 640, 20480, mb + MB_KV1);
    mbar_wait_u(mb + MB_Q, 0);
    if (warp < 2) bulk_ne(qs + 16384 + warp * 8192, G->q + ((hg + warp) * S_ + tg * 128 + 64) * 8, 8192, mb + MB_Q + 8);
    if (warp == 0) bulk_ne(sa + SM_KV + 30720, G->kv + 1920, 133120, mb + MB_KV + 8);
    {
      mbar_wait_u(mb + MB_KV, 0);
      const float rk = key_radius(mb + MS_RSQ, lane);
      mbar_wait_u(mb + MB_Q + 8, 0);
#pragma unroll 1
      for (int w = 0; w < 4; w++) {
        uint32_t a[3], qb[4], e0, e1;
        q_addr(qs + 16384, hg, w, warp, lane, a);
        const uint32_t wt = load_q(a, qb);
        if (bound_q(qb, wt, rk, c, e0, e1)) asm volatile("st.shared.u8 [%0], 1;" ::"r"(mb + MS_BAD + (w * 4 + warp) * 2 + 1) : "memory");
        const int td = w * 128 + warp * 32 + lane;
        sts128(sa + SM_QB + td * 16, qb[0], qb[1], qb[2], qb[3]);
        if (c < 2) sts64f(sa + SM_QB + 8192 + (td >> 2) * 16 + c * 8, __uint_as_float(e0), __uint_as_float(e1));
      }
      __syncwarp();
      mbar_arrive_e(mb + MB_QC);
    }
    if (warp == 0) {
      if (lane < 8) map_prefetch(&M.wo + lane);
      l2_prefetch_e(P.wg + b * 20736, 41472); l2_prefetch_e(P.wu + b * 20736, 41472); l2_prefetch_e(P.wd + b * 20736, 41472);
      mbar_wait_u(mb + MB_QC, 0);
      tma4_e(sa + SM_WO, &M.wo, 0, 0, 0, hg * 9, mb + MB_WO);
      mbar_wait_u(mb + MB_O1, 0);
#pragma unroll 1
      for (int j = 0; j < 16; j++) {
        const uint32_t need = 14 - ((0xeeddccba97654310ull >> (4 * j)) & 15);
#pragma unroll 1
        for (int it = 0; it < (1 << 22) && !__all_sync(0xffffffffu, lds32(mb + MS_PROG + (lane & 15) * 4) <= need); it++) __nanosleep(200);
        if (j < 2) tma4_e(sa + SM_WO + (6 + 2 * j) * 9216, &M.wo7 + j, 0, j * 16, j ? 0 : 24, hg * 9, mb + MB_WO);
        else if (j == 2) tma2_e(sa + SM_XT, &M.xt, hg * 72, tg * 128, mb + MB_XT);
        else if (j < 11) tma2_e(sa + SM_GATE + (j - 3) * 11520, &M.g + ((j - 3) >> 2), fc, ((j - 3) & 3) * 144, mb + MB_GU);
        else tma2_e(sa + SM_DOWN + (j - 11) * 5120, &M.d, (j - 11) * 64, fc, mb + MB_DOWN);
      }
    } else if (warp == 1) {
      {
        uint4* z = G->o + (tg * 2 + 1) * 4608 + lane;
#pragma unroll 1
        for (int i = 0; i < 16; i++) stg4(z + hg * 512 + i * 32, 0u, 0u, 0u, 0u);
#pragma unroll 1
        for (int i = 0; i < 4; i++) stg2(reinterpret_cast<uint2*>(z + (32 + (hg >> 1)) * 128 + i * 32) + (hg & 1), 0u, 0u);
#pragma unroll 1
        for (int i = 0; i < 18; i++) stg4(G->yp + (i * 4 + (lane >> 3)) * 1024 + b * 8 + (lane & 7), 0u, 0u, 0u, 0u);
        asm volatile("fence.acq_rel.gpu;" ::: "memory");
        __syncwarp();
        mbar_arrive_e(mb + MB_QC);
      }
      mbar_wait_u(mb + MB_O1, 0);
      const bool held = __any_sync(0xffffffffu, lds32(mb + MS_BAD + (lane & 7) * 4) & 0x00ff00ffu);
      if (!held) cnt_arrive_e(cnt);
      bar_sync(B_END, 576);
      if (held) cnt_arrive_e(cnt);
      mbar_wait_u(mb + MB_G3, 0);
      cnt_wait_u(&G->cnt[0], 200);
#pragma unroll 1
      for (int j = 5; j < 9; j++) tma2_e(sa + (j < 7 ? SM_DOWN + j * 5120 : (j - 7) * 5120), &M.d, j * 64, fc, mb + MB_DOWN);
      cnt_wait_u(&G->cnt[0], 256);
      PROF_C(18, 544);
      bar_arrive(B_SEL, 544);
    } else {
      if (warp == 2) {
        float wsum = 0.f;
#pragma unroll 1
        for (int j = 0; j < 9; j++) {
          const int i = j * 32 + lane;
          const uint32_t w = __ldg(reinterpret_cast<const uint32_t*>(P.wr) + i);
          wsum += bf_lo(w) + bf_hi(w);
          if ((unsigned)(i - hg * 36) < 36u) sts64f(mb + MS_WR + (i - hg * 36) * 8, bf_lo(w), bf_hi(w));
        }
#pragma unroll
        for (int o = 16; o; o >>= 1) wsum += __shfl_xor_sync(0xffffffffu, wsum, o);
        sts32f(mb + MS_WR + 288, wsum);
        __syncwarp();
        mbar_arrive_e(mb + MB_XT);
        mbar_wait_u(mb + MB_O1, 0);
        __nanosleep(2000);
      } else {
        bar_sync(B_END, 576);
        cnt_arrive_relaxed_e(cnt + 32);
        PROF_C(54, 608);
      }
      const int tile = warp - 2;
      cnt_wait_u(cnt + tile * 32, 8);
      bar_arrive(B_O + tile, 288);
      bar_sync(B_H + tile, 288);
      tma2_store_e(&M.h, hg * 72, tile * 1024 + tg * 64, sa + SM_XT + tile * 9216);
      bulk_wait_all();
      cnt_arrive_relaxed_e(&G->cnt[0]);
    }
    bar_sync(0, 640);
    uint4* op = reinterpret_cast<uint4*>(P.out) + tg * 128 * 72 + hg * 9;
#pragma unroll 3
    for (int id = tid & 127; id < 1152; id += 128) {
      const int row = (id * 7282) >> 16;
      const uint4 v = lds128(sa + SM_XT + id * 16);
      uint32_t skip;
      asm volatile("ld.shared.u8 %0, [%1];" : "=r"(skip) : "r"(mb + MS_ROW + row));
      if (!skip) op[row * 63 + id] = v;
    }
    if (tid < 520) reinterpret_cast<uint4*>(G->st0)[b * 8 + lane] = make_uint4(0u, 0u, 0u, 0u);
    return;
  }
  asm volatile("setmaxnreg.inc.sync.aligned.u32 112;");

  const int tl = (wg >> 1) ^ 1, kh = wg & 1;
  int hidx;
  uint32_t xt, zero;
  const uint4 *op, *tp;
  uint32_t unsafe;
  {
    uint32_t q0[4], q1[4], m2, half;
    uint32_t qa[3];
    q_addr(qs, hg, wg, warp, lane, qa);
    keep(qa[0]); keep(qa[1]); keep(qa[2]);
    float o[12]; uint32_t s[32];
#pragma unroll
    for (int i = 0; i < 12; i++) o[i] = 0.f;
#pragma unroll
    for (int i = 0; i < 32; i++) s[i] = 0u;
    pin(o); pin(s);
    const uint32_t klo = ((sa + SM_KV) >> 4 & 0x3fff) | (8u << 16), vbase = ((sa + SM_KV + 256 - (LV == 5 ? 1280 : 0)) >> 4 & 0x3fff) | (40u << 16);
    uint32_t vlo = vbase;
    constexpr uint32_t V2K = (LV == 5 ? 720 : 640) - 16 - (32u << 16);
    uint32_t v2k = V2K;
    uint32_t prog = mb + MS_PROG + wid * 4;
    keep(prog);
    bar_sync(0, 640);
    asm volatile("ld.volatile.shared.v4.u32 {%0,%1,%2,%3}, [%4];" : "=r"(q1[2]), "=r"(q1[3]), "=r"(m2), "=r"(half) : "r"(mb + MS_K) : "memory");
    uint4* opub = G->o + (tg * 9216 + (hg * 4 + wg) * 128 + (tid & 127) + q1[2]);
    uint2* tpub = reinterpret_cast<uint2*>(G->o) + ((tg * 9216 + (32 + (hg >> 1)) * 128 + (tid & 124) + wg) * 2 + (hg & 1) + q1[2]);
    if (c != 2) tpub = nullptr;
    keepp(opub); keepp(tpub);
    mbar_wait_u(mb + MB_KV, 0);
    const float rk = key_radius(mb + MS_RSQ, lane);
    mbar_wait_u(mb + MB_Q + ((__float_as_uint(rk) ^ (uint32_t)(uintptr_t)opub ^ (uint32_t)(uintptr_t)tpub) & q1[2]), 0);
    PROF_C(59, 128);
    const uint32_t wt = load_q(qa, q0);
    wg_fence();
    wg_qk_n128(s, q0, dsc(klo, 40), 0);
    if (bound_q(q0, wt, rk, c, q1[0], q1[1])) asm volatile("st.shared.u8 [%0], 1;" ::"r"(mb + MS_BAD + wid * 2) : "memory");
    pin(q1);
    wg_fence();
    wg_qk_n128(s, q1, dsc(klo, 40) + 16, 1);
    wg_commit();
    mbar_arrive_e(mb + MB_QC);
    mbar_wait_u(mb + MB_KV1, 0);
    PROF_C(11, 128);
    auto publish = [&](int pass, uint32_t dep) {
      uint32_t was;
      asm volatile("ld.shared.u16 %0, [%1];" : "=r"(unsafe) : "r"(mb + MS_BAD + wid * 2 + dep));
      was = unsafe & (pass ? 0xff00u : 0xffu);
      wg_wait<0>(); pin(o);
      const float l0 = __shfl_sync(0xffffffffu, o[0], 3, 4), l1 = __shfl_sync(0xffffffffu, o[2], 3, 4);
      const float i0 = rcp(l0), i1 = rcp(l1);
      const uint32_t bad = __any_sync(0xffffffffu, was || !(fminf(l0, l1) >= L_MIN) || !(l0 + l1 < 1e30f));
      asm volatile("{.reg .pred p, q; .reg .b128 t; .reg .b64 u; setp.eq.u32 p, %9, 0; setp.ne.and.u64 q, %10, 0, p;\n"
                   "mov.b128 t, {%2,%3,%4,%5}; @p st.relaxed.gpu.global.b128 [%0], t;\n"
                   "mov.b64 u, {%6,%7}; @q st.relaxed.gpu.global.b64 [%1], u; @!p st.shared.u8 [%8], 1;}"
                   ::"l"(opub + pass * 4608), "l"(tpub + pass * 9216), "r"(nz(pk_bf(o[4] * i0, o[5] * i0))), "r"(pk_bf(o[6] * i1, o[7] * i1)),
                     "r"(pk_bf(o[8] * i0, o[9] * i0)), "r"(pk_bf(o[10] * i1, o[11] * i1)), "r"(nz(pk_bf(o[0] * i0, o[1] * i0))), "r"(pk_bf(o[2] * i1, o[3] * i1)),
                     "r"(mb + MS_BAD + wid * 2 + pass), "r"(bad), "l"(tpub) : "memory");
      unsafe |= bad << 8;
    };
    uint32_t segs = 0x0f010d02u;
    const uint32_t vhi = __shfl_sync(0xffffffffu, 8 + q1[2], 0), khi = __shfl_sync(0xffffffffu, 40 + q1[2], 0);
#pragma unroll 1
    while (true) {
      uint32_t n = segs & 255u;
#pragma unroll 1
      do {
        wg_wait<0>(); pin(s);
        sts32(prog, n);
        exp_pv(s, o, dsc(vlo, vhi) + 80, m2, half);
        const uint64_t dk = dsc(vlo + v2k, khi);
        wg_qk_n128(s, q0, dk, 0);
        wg_qk_n128(s, q1, dk + 16, 1);
        vlo += 640;
        wg_commit();
      } while (--n);
      segs >>= 8;
      if (segs > 0xffffu) {
        mbar_wait_u(mb + MB_KV + 8, 0);
      } else if (segs > 0xffu) {
        int td;
        asm volatile("mov.u32 %0, %%tid.x;" : "=r"(td));
        mbar_wait_u(mb + MB_QC, 0);
        wg_wait<0>(); pin(q0); pin(q1);
        asm volatile("ld.shared.v4.u32 {%0,%1,%2,%3}, [%4];" : "=r"(q0[0]), "=r"(q0[1]), "=r"(q0[2]), "=r"(q0[3]) : "r"(sa + SM_QB + td * 16));
        asm volatile("{.reg .pred p; setp.eq.u32 p, %3, 0; @p ld.shared.v2.u32 {%0,%1}, [%2];}" : "+r"(q1[0]), "+r"(q1[1]) : "r"(sa + SM_QB + 8192 + (td >> 2) * 16 + (td & 1) * 8), "r"(td & 2));
        v2k = V2K - 10240;
      } else if (segs) {
        publish(0, 0);
#pragma unroll
        for (int i = 0; i < 12; i++) o[i] = __uint_as_float(q1[2]);
        vlo = vbase; v2k = V2K;
        sts32(prog, 15);
        __syncwarp();
        mbar_arrive_e(mb + MB_O1);
        PROF_C(12, 128);
      } else break;
    }
    {
      wg_wait<0>(); pin(s);
      sts32(prog, 0);
      exp_pv(s, o, LV == 5 ? dsc(vbase + 9680, 8) : dsc(vlo, 8), m2, half);
      wg_commit();
      asm volatile("mov.u32 %0, %%tid.x;" : "=r"(tid));
      lane = tid & 31; c = lane & 3; r = lane >> 2;
      const int hrow = tl * 64 + warp * 16 + kh * 8 + r;
      hidx = tl * 960 + tg * 64 + hrow;
      xt = sa + SM_XT + hrow * 144 + c * 4;
      op = G->o + ((tg * 2 + tl) * 4608 + kh * 2048 + (tid & 127));
      keepp(op);
      tp = op + (4096 - kh * 1792);
      keepp(tp);
      zero = lds32(mb + MS_K);
      publish(1, (xt ^ hidx ^ (uint32_t)(uintptr_t)tp ^ (uint32_t)((uintptr_t)tp >> 32)) & zero);
    }
  }
  if (__any_sync(0xffffffffu, unsafe != 0u)) {
#pragma unroll 1
    for (int pass = 0; pass < 2; pass++)
      if ((unsafe >> (8 * pass)) & 1u) exact_tile(G, P.x, P.wq, tg * 2 + pass, hg * 4 + wg);
  }
  bar_arrive(B_END, 576);
  PROF_C(13, 128);

  uint32_t hreg[9];
  {
    mbar_wait_u(mb + MB_XT, 0);
    uint32_t xw[9];
#pragma unroll
    for (int i = 0; i < 9; i++) xw[i] = lds32(xt + i * 16);
    mbar_wait_u(mb + MB_WO, 0);
    float d[36];
    bar_sync(B_O + tl, 288);
    PROF_C(14, 128);
#pragma unroll 1
    for (int it = 0; it < (1 << 20); it++) {
      uint32_t a[12][4];
#pragma unroll
      for (int i = 0; i < 12; i++) ldg4(a[i], op + i * 128);
#pragma unroll
      for (int i = 0; i < 9; i++) {
        asm volatile("shl.b32 %0, %4, 16; and.b32 %1, %4, 0xffff0000; mov.b32 %2, %5; mov.b32 %3, %5;"
                     : "=f"(d[4 * i]), "=f"(d[4 * i + 1]), "=f"(d[4 * i + 2]), "=f"(d[4 * i + 3]) : "r"(xw[i]), "r"(zero));
      }
      const uint32_t wlo = (((sa + SM_WO) >> 4 & 0x3fff) | (8u << 16)) + (it >> 24);
      const uint64_t db = dsc(wlo + kh * 256, 384u), d3 = dsc(wlo + (kh ? 3456 : 128), kh ? 128u : 384u), dt = dsc(wlo + 4608 + kh * 32, 64u);
#pragma unroll
      for (int j = 0; j < 2; j++) {
        wg_fence();
#pragma unroll
        for (int i = 3 * j; i < 3 * j + 3; i++) wg_rs_n72_tB(d, a[i], db + i * 16, 1);
      }
      wg_commit();
      uint32_t ok = min(min(min(a[0][0], a[1][0]), min(a[2][0], a[3][0])), min(a[4][0], a[5][0]));
      const uint32_t zz = ok & zero;
      wg_wait<0>(); pin(d);
      uint32_t e[6][4];
#pragma unroll
      for (int i = 0; i < 6; i++) ldg4(e[i], (i < 4 ? op + (12 + i) * 128 : tp + (i - 4) * 128) + zz);
      __syncwarp();
      wg_fence();
#pragma unroll
      for (int i = 6; i < 12; i++) wg_rs_n72_tB(d, a[i], i < 8 ? db + i * 16 : d3 + (i - 8) * 16, 1);
      wg_fence();
#pragma unroll
      for (int i = 0; i < 6; i++) wg_rs_n72_tB(d, e[i], i < 4 ? d3 + (4 + i) * 16 : dt + (i - 4) * 16, 1);
      wg_commit();
#pragma unroll
      for (int i = 0; i < 6; i++) ok = min(ok, min(a[6 + i][0], e[i][0]));
      ok = min(ok, min(e[4][2], e[5][2]));
      int redo;
      asm volatile("{.reg .pred p,q; setp.eq.u32 p, %1, 0; bar.red.or.pred q, %2, 256, p; vote.sync.all.pred q, q, 0xffffffff; selp.u32 %0,1,0,q;}" : "=r"(redo) : "r"(ok), "r"(B_EX + tl) : "memory");
      wg_wait<0>(); pin(d);
      if (!redo) break;
    }
    const uint32_t ex = kh ? xt - 1152 : xt + 1152;
    float4* stp = &G->st2[hidx];
    keepp(stp);
    PROF_C(15, 0); PROF_C(16, 384);
#pragma unroll
    for (int i = 0; i < 9; i++) sts32(ex + i * 16, pk_bf(d[4 * i + 2], d[4 * i + 3]));
    mbar_arrive_e(mb + MB_G3);
    bar_sync(B_EX + tl, 256);
    float s0 = 0.f, s1 = 0.f, v0 = 0.f, v1 = 0.f, t0 = 0.f, t1 = 0.f;
#pragma unroll
    for (int i = 0; i < 9; i++) {
      const uint32_t e = lds32(xt + i * 16);
      const float2 w = lds64f(mb + MS_WR + c * 8 + i * 32);
      const float a0 = d[4 * i] + bf_lo(e), a1 = d[4 * i + 1] + bf_hi(e);
      hreg[i] = pk_bf(a0, a1);
      s0 += a0; s1 += a1; v0 += a0 * a0; v1 += a1 * a1; t0 += a0 * w.x; t1 += a1 * w.y;
    }
    s0 += s1; v0 += v1; t0 += t1;
#pragma unroll
    for (int o = 1; o < 4; o <<= 1) {
      s0 += __shfl_xor_sync(0xffffffffu, s0, o); v0 += __shfl_xor_sync(0xffffffffu, v0, o); t0 += __shfl_xor_sync(0xffffffffu, t0, o);
    }
    if (c == 0) asm volatile("red.global.add.v4.f32 [%0], {%1,%2,%3,%4};" ::"l"(stp), "f"(s0), "f"(v0), "f"(t0), "f"(1.f) : "memory");
    PROF_C(17, 0);
#pragma unroll
    for (int i = 0; i < 9; i++) sts32(xt + i * 16, hreg[i]);
    fence_async_smem();
  }
  bar_arrive(B_H + tl, 288);
  uint32_t af[12][4];
  {
    mbar_wait_u(mb + MB_GU, 0);
    const int w15 = min(wid, 14), mt = w15 % 5, kq = w15 / 5, mi = lane >> 3;
    const uint32_t a = sa + ((mi & 1) ? SM_UP : SM_GATE) + (kq * 192 + (mi >> 1) * 8 + (lane & 7)) * 80 + mt * 16;
#pragma unroll
    for (int i = 0; i < 12; i++) ldsm4t(af[i], a + i * 1280);
  }
  {
    const float wsum = __uint_as_float(lds32(mb + MS_WR + 288));
    const int tk = (tid & 255) + tl * 1024;
    const float4* sp = &G->st2[tk];
    const uint32_t lst = mb + MS_RSQ + tl * 256;
    uint32_t mylist = lst + (wid & 7) * 32, lt;
    asm("mov.u32 %0, %%lanemask_lt;" : "=r"(lt));
    keepp(sp);
    sts32(mylist + (lane & 7) * 4, 0u);
    PROF_C(29, 128); PROF_C(49, 384);
    mbar_wait_u(mb + MB_G3, 0);
    PROF_C(30, 128);
    float4 st[4];
#pragma unroll
    for (int i = 0; i < 4; i++) st[i].w = 0.f;
#pragma unroll 1
    for (int it = 0; it < (1 << 22); it++) {
#pragma unroll
      for (int i = 0; i < 4; i++)
        asm volatile("{.reg .pred p; setp.neu.f32 p, %3, 0f41000000; @p ld.relaxed.gpu.global.v4.f32 {%0,%1,%2,%3}, [%4];}" : "+f"(st[i].x), "+f"(st[i].y), "+f"(st[i].z), "+f"(st[i].w) : "l"(sp + i * 256) : "memory");
      if (__all_sync(0xffffffffu, st[0].w + st[1].w + st[2].w + st[3].w == 32.f)) break;
    }
    PROF_C(19, 128); PROF_C(50, 384);
    uint32_t key[5], thr;
#pragma unroll
    for (int i = 0; i < 4; i++) {
      const float m = st[i].x * (1.f / D_), rs = rsq(fmaxf(st[i].y * (1.f / D_) - m * m, 0.f) + 1e-5f);
      const uint32_t u = __float_as_uint((st[i].z - m * wsum) * rs);
      key[i] = ((u ^ (((int)u >> 31) | 0x80000000u)) & ~0x7ffu) | (uint32_t)(tk + i * 256);
      sts64f(sa + FS_TAB + (tk + i * 256) * 8, m, rs);
    }
    if (!tl) {
      sts32(mb + MS_MAX + (wid & 7) * 4, __reduce_max_sync(0xffffffffu, max(max(key[0], key[1]), max(key[2], key[3]))));
      bar_sync(B_EX, 256);
      thr = max(__reduce_min_sync(0xffffffffu, lds32(mb + MS_MAX + (lane & 7) * 4)), 1u);
      key[4] = 0u;
    } else {
      bar_sync(B_THR, 512);
      thr = lds32(mb + MS_SEL - 4);
      key[4] = lds32(mb + MS_SEL - 32 + wid * 4);
      if (lane) key[4] = 0u;
    }
    uint32_t bl[5];
#pragma unroll 1
    while (true) {
      int n = 0;
#pragma unroll
      for (int i = 0; i < 5; i++) { bl[i] = __ballot_sync(0xffffffffu, key[i] >= thr); n += __popc(bl[i]); }
      if (n <= 8) break;
      uint32_t mn = 0xffffffffu;
#pragma unroll
      for (int i = 0; i < 5; i++) mn = min(mn, key[i] >= thr ? key[i] : 0xffffffffu);
      thr = __reduce_min_sync(0xffffffffu, mn) + 1;
    }
#pragma unroll
    for (int i = 0; i < 5; i++) {
      if (key[i] >= thr) sts32(mylist + __popc(bl[i] & lt) * 4, key[i]);
      mylist += __popc(bl[i]) * 4;
    }
    bar_sync(B_EX + tl, 256);
    const uint32_t k = lds32(lst + (wid & 7) * 32 + r * 4);
    int rk[4] = {0, 0, 0, 0};
#pragma unroll
    for (int i = 0; i < 4; i++) {
      const uint4 v = lds128(lst + c * 16 + i * 64);
      asm("{.reg .pred p0,p1,p2,p3; setp.gt.u32 p0,%4,%8; setp.gt.u32 p1,%5,%8; setp.gt.u32 p2,%6,%8; setp.gt.u32 p3,%7,%8;"
          "@p0 add.u32 %0,%0,1; @p1 add.u32 %1,%1,1; @p2 add.u32 %2,%2,1; @p3 add.u32 %3,%3,1;}"
          : "+r"(rk[0]), "+r"(rk[1]), "+r"(rk[2]), "+r"(rk[3]) : "r"(v.x), "r"(v.y), "r"(v.z), "r"(v.w), "r"(k));
    }
    int rr = (rk[0] + rk[1]) + (rk[2] + rk[3]);
    rr += __shfl_xor_sync(0xffffffffu, rr, 1);
    rr += __shfl_xor_sync(0xffffffffu, rr, 2);
    if (rr < 8) sts32(mb + MS_SEL - 32 + tl * 32 + rr * 4, k);
    if (!tl) bar_arrive(B_THR, 512);
    PROF_C(20, 0); PROF_C(52, 384);
  }
  uint32_t da[4][2][4], db[4][2];
  auto load_down = [&]() {
    mbar_wait_u(mb + MB_DOWN, 0);
    const int mi = lane >> 3;
    const uint32_t a = sa + (wid < 14 ? SM_DOWN + (wid - 7) * 5120 : (wid - 14) * 5120) + (lane & 7) * 128 + (((mi & 1) ^ (lane & 7)) << 4);
#pragma unroll
    for (int j = 0; j < 4; j++) {
      ldsm4t(da[j][0], (a ^ (j * 32)) + (mi >> 1) * 1024);
      ldsm4t(da[j][1], (a ^ (j * 32)) + (mi >> 1) * 1024 + 2048);
      ldsm2t(db[j], (a ^ (j * 32)) + 4096);
    }
  };
  const int gt = (wid & 1) * 4 + (lane >> 3);
  const uint4* hp = reinterpret_cast<const uint4*>(G->h) + (wid >> 1) * 8 + (lane & 7);
  const uint32_t xs = sa + FS_XS + gt * 1168 + (wid >> 1) * 128 + (lane & 7) * 16;
  bar_sync_after(B_SEL, 544, (uint32_t)(uintptr_t)hp ^ (uint32_t)((uintptr_t)hp >> 32) ^ xs, zero);
  PROF_C(21, 128);
  {
    const uint32_t tk = lds32(mb + MS_SEL + gt * 4) & 0x7ffu;
    uint32_t hv[4], hv2[4];
    ldg4(hv, hp + tk * 72);
    if (wid >= 14) ldg4(hv2, hp + tk * 72 + 8);
    const float2 sg = lds64f(sa + FS_TAB + tk * 8);
    const uint32_t xa = sa + FS_XS + (lane & 7) * 1168 + (wid / 5) * 384 + (lane >> 3) * 16, pp = sa + FS_PART + tid * 16;
    auto put = [&](const uint32_t (&w)[4], uint32_t dst) {
      const float rs = sg.y, g = -sg.x * rs;
      sts128(dst, pk_bf(bf_lo(w[0]) * rs + g, bf_hi(w[0]) * rs + g), pk_bf(bf_lo(w[1]) * rs + g, bf_hi(w[1]) * rs + g),
             pk_bf(bf_lo(w[2]) * rs + g, bf_hi(w[2]) * rs + g), pk_bf(bf_lo(w[3]) * rs + g, bf_hi(w[3]) * rs + g));
      sts128(dst + (FS_HS - FS_XS), w[0], w[1], w[2], w[3]);
    };
    put(hv, xs);
    if (wid >= 14) put(hv2, xs + 128);
    bar_sync_after(B_XS, 512, xa ^ pp, zero);
    PROF_C(22, 128);
    {
      float dd[4][4] = {};
      uint32_t bb[6][4];
#pragma unroll
      for (int i = 0; i < 6; i++) ldsm4(bb[i], xa + i * 64);
#pragma unroll
      for (int i = 0; i < 12; i++) mma16(dd[i & 3], af[i], bb[i >> 1][(i & 1) * 2], bb[i >> 1][(i & 1) * 2 + 1]);
      sts128f(pp, (dd[0][0] + dd[1][0]) + (dd[2][0] + dd[3][0]), (dd[0][1] + dd[1][1]) + (dd[2][1] + dd[3][1]),
              (dd[0][2] + dd[1][2]) + (dd[2][2] + dd[3][2]), (dd[0][3] + dd[1][3]) + (dd[2][3] + dd[3][3]));
    }
    if (wid < 5) {
      bar_sync(B_PART, 512);
      const float4 p0 = lds128f(pp), p1 = lds128f(pp + 2560), p2 = lds128f(pp + 5120);
      const float g0 = p0.x + p1.x + p2.x, g1 = p0.y + p1.y + p2.y, u0 = p0.z + p1.z + p2.z, u1 = p0.w + p1.w + p2.w;
      const uint32_t a = movm(pk_bf(g0 * u0 * sigm(g0), g1 * u1 * sigm(g1)));
      sts32(sa + FS_ACT + tid * 4, (wid == 0 && (b & 1)) ? 0u : a);
      bar_arrive(B_ACT, 448);
    } else {
      bar_arrive(B_PART, 512);
      if (wid >= 7) {
        load_down();
        uint4* yp = G->yp + ((wid - 7) * 8 + (lane >> 3)) * 1024 + b * 8 + (lane & 7);
        const uint32_t aa = sa + FS_ACT + lane * 4;
        bar_sync_after(B_ACT, 448, (uint32_t)(uintptr_t)yp ^ (uint32_t)((uintptr_t)yp >> 32) ^ aa, zero);
        PROF_C(23, 256);
        uint32_t bb[5], y[8];
#pragma unroll
        for (int i = 0; i < 5; i++) bb[i] = lds32(aa + i * 128);
#pragma unroll
        for (int j = 0; j < 4; j++) {
          float d[4] = {0.f, 0.f, 0.f, 0.f};
          mma16(d, da[j][0], bb[0], bb[1]);
          mma16(d, da[j][1], bb[2], bb[3]);
          mma8(d, db[j], bb[4]);
          y[2 * j] = pk_bf(d[0], d[1]); y[2 * j + 1] = pk_bf(d[2], d[3]);
        }
        stg4(yp, nz(y[0]), y[1], y[2], y[3]);
        stg4(yp + 4096, nz(y[4]), y[5], y[6], y[7]);
        PROF_C(24, 256);
      } else if ((lane & 7) == 0 && ((tk >> 6) & 15) == tg) {
        asm volatile("st.shared.u8 [%0], 1;" ::"r"(mb + MS_ROW + (tk >> 10) * 64 + (tk & 63)) : "memory");
      }
    }
    {
      const float2 so = lds64f(sa + FS_TAB + hidx * 8);
      const float f = 1.f + so.y, g = -so.x * so.y;
#pragma unroll
      for (int i = 0; i < 9; i++) sts32(xt + i * 16, pk_bf(bf_lo(hreg[i]) * f + g, bf_hi(hreg[i]) * f + g));
    }
    bar_arrive(0, 640);
    if ((b & 15) < 9) {
      const int b = (blockIdx.x >> 4) * 9 + (blockIdx.x & 15);
      const uint4* p = G->yp + b * 1024 + tid;
      const int fl = (b & 3) * 8 + ((tid & 63) >> 3), col = (b >> 2) * 32 + (tid & 6) * 4 + (fl >> 2), slot = (fl & 3) * 2 + (tid & 1);
      const uint32_t key = lds32(mb + MS_SEL + slot * 4), k = key & 0x7ffu, kr = (key & ~0x7ffu) | 0x400u;
      const float sig = sigm(__uint_as_float(kr ^ (~((int)kr >> 31) | 0x80000000u)));
      const float2 so = lds64f(sa + FS_TAB + k * 8);
      uint32_t hb;
      asm volatile("ld.shared.u16 %0, [%1];" : "=r"(hb) : "r"(sa + FS_HS + slot * 1168 + col * 2));
      uint32_t v0[4] = {0u, 0u, 0u, 0u}, v1[4] = {0u, 0u, 0u, 0u};
      const float base = bf_lo(hb) * (1.f + so.y) - so.x * so.y;
      __nv_bfloat16* op = P.out + (((k & 960u) * 2 + ((k >> 4) & 64u) + (k & 63u)) * D_ + col);
      bar_sync_after(B_EX + 1, 512, __float_as_uint(sig) ^ __float_as_uint(base) ^ (uint32_t)(uintptr_t)op ^ (uint32_t)(uintptr_t)p, zero);
      PROF_C(53, 128);
#pragma unroll 1
      for (int it = 0; it < (1 << 22); it++) {
        if (!v0[0]) ldg4(v0, p);
        if (!v1[0]) ldg4(v1, p + 512);
        if (__all_sync(0xffffffffu, min(v0[0], v1[0]) != 0u)) break;
      }
      PROF_C(26, 128);
      float a[8], c4[4], c2[2];
#pragma unroll
      for (int j = 0; j < 4; j++) { a[2 * j] = bf_lo(v0[j]) + bf_lo(v1[j]); a[2 * j + 1] = bf_hi(v0[j]) + bf_hi(v1[j]); }
#pragma unroll
      for (int j = 0; j < 4; j++) c4[j] = ((lane & 16) ? a[4 + j] : a[j]) + __shfl_xor_sync(0xffffffffu, (lane & 16) ? a[j] : a[4 + j], 16);
#pragma unroll
      for (int j = 0; j < 2; j++) c2[j] = ((lane & 8) ? c4[2 + j] : c4[j]) + __shfl_xor_sync(0xffffffffu, (lane & 8) ? c4[j] : c4[2 + j], 8);
      sts64f(sa + FS_RED + wid * 256 + ((lane & 7) * 8 + (lane >> 4) * 4 + ((lane >> 3) & 1) * 2) * 4, c2[0], c2[1]);
      if (wid >= 2) bar_arrive(B_PART, 512);
      else {
        bar_sync(B_PART, 512);
        float s4[4] = {0.f, 0.f, 0.f, 0.f};
#pragma unroll
        for (int i = 0; i < 16; i++) s4[i & 3] += __uint_as_float(lds32(sa + FS_RED + i * 256 + tid * 4));
        *op = __float2bfloat16(base + sig * ((s4[0] + s4[1]) + (s4[2] + s4[3])));
      }
      PROF_C(27, 0);
    }
    PROF_T(25, 128);
  }
}

typedef CUresult (*EncodeFn)(CUtensorMap*, CUtensorMapDataType, cuuint32_t, void*, const cuuint64_t*, const cuuint64_t*,
                             const cuuint32_t*, const cuuint32_t*, CUtensorMapInterleave, CUtensorMapSwizzle,
                             CUtensorMapL2promotion, CUtensorMapFloatOOBfill);

void make_map(EncodeFn enc, CUtensorMap* m, const void* p, int rank, const cuuint64_t* gd, const cuuint64_t* gs,
              const cuuint32_t* bx, CUtensorMapSwizzle sw) {
  const cuuint32_t es[4] = {1, 1, 1, 1};
  enc(m, CU_TENSOR_MAP_DATA_TYPE_BFLOAT16, rank, const_cast<void*>(p), gd, gs, bx, es, CU_TENSOR_MAP_INTERLEAVE_NONE, sw,
      CU_TENSOR_MAP_L2_PROMOTION_L2_128B, CU_TENSOR_MAP_FLOAT_OOB_FILL_NONE);
}

}

extern "C" void kernel_launch(void* const* d_in, const int* in_sizes, int n_in, void* d_out, int out_size) {
  (void)in_sizes; (void)n_in; (void)out_size;
  void* fn = nullptr;
  cudaDriverEntryPointQueryResult qr;
  cudaGetDriverEntryPoint("cuTensorMapEncodeTiled", &fn, cudaEnableDefault, &qr);
  EncodeFn enc = (EncodeFn)fn;
  CUtensorMap mx, mwq;
  Maps M;
  Scratch* G = nullptr;
  cudaGetSymbolAddress((void**)&G, g_s);
  void* h_ptr = G->h;
  { const cuuint64_t gd[] = {576, 2048}, gs[] = {1152}; const cuuint32_t bx[] = {64, 88}; make_map(enc, &mx, d_in[0], 2, gd, gs, bx, CU_TENSOR_MAP_SWIZZLE_128B); }
  { const cuuint64_t gd[] = {576, 576}, gs[] = {1152}; const cuuint32_t bx[] = {64, 64}; make_map(enc, &mwq, d_in[1], 2, gd, gs, bx, CU_TENSOR_MAP_SWIZZLE_128B); }
  { const cuuint64_t gd[] = {8, 18, 32, 72}, gs[] = {1152, 20736, 16}; const cuuint32_t b0[] = {8, 16, 24, 9}, b1[] = {8, 16, 8, 9}, b2[] = {8, 2, 32, 9};
    make_map(enc, &M.wo, d_in[4], 4, gd, gs, b0, CU_TENSOR_MAP_SWIZZLE_NONE); make_map(enc, &M.wo7, d_in[4], 4, gd, gs, b1, CU_TENSOR_MAP_SWIZZLE_NONE); make_map(enc, &M.wt, d_in[4], 4, gd, gs, b2, CU_TENSOR_MAP_SWIZZLE_NONE); }
  { const cuuint64_t gd[] = {4608, 576}, gs[] = {9216}; const cuuint32_t bx[] = {40, 144};
    make_map(enc, &M.g, d_in[7], 2, gd, gs, bx, CU_TENSOR_MAP_SWIZZLE_NONE); make_map(enc, &M.u, d_in[8], 2, gd, gs, bx, CU_TENSOR_MAP_SWIZZLE_NONE); }
  { const cuuint64_t gd[] = {576, 4608}, gs[] = {1152}; const cuuint32_t bx[] = {64, 40}; make_map(enc, &M.d, d_in[9], 2, gd, gs, bx, CU_TENSOR_MAP_SWIZZLE_128B); }
  { const cuuint64_t gd[] = {576, 2048}, gs[] = {1152}; const cuuint32_t b1[] = {72, 128}, b2[] = {72, 64};
    make_map(enc, &M.xt, d_in[0], 2, gd, gs, b1, CU_TENSOR_MAP_SWIZZLE_NONE); make_map(enc, &M.h, h_ptr, 2, gd, gs, b2, CU_TENSOR_MAP_SWIZZLE_NONE); }
  Params P;
  P.x = (const __nv_bfloat16*)d_in[0]; P.wq = (const __nv_bfloat16*)d_in[1]; P.wr = (const __nv_bfloat16*)d_in[6]; P.G = G; P.out = (__nv_bfloat16*)d_out;
  P.wg = (const __nv_bfloat16*)d_in[7]; P.wu = (const __nv_bfloat16*)d_in[8]; P.wd = (const __nv_bfloat16*)d_in[9];
  cudaFuncSetAttribute(pre_kernel, cudaFuncAttributeMaxDynamicSharedMemorySize, SM1_TOTAL);
  cudaFuncSetAttribute(main_kernel, cudaFuncAttributeMaxDynamicSharedMemorySize, SM_TOTAL);
  pre_kernel<<<132, NTHR, SM1_TOTAL, cudaStreamPerThread>>>(G, (const __nv_bfloat16*)d_in[2], (const __nv_bfloat16*)d_in[3], mx, mwq);
  cudaLaunchAttribute at[1];
  at[0].id = cudaLaunchAttributeProgrammaticStreamSerialization; at[0].val.programmaticStreamSerializationAllowed = 1;
  cudaLaunchConfig_t cfg = {};
  cfg.gridDim = 128; cfg.blockDim = 640; cfg.dynamicSmemBytes = SM_TOTAL; cfg.stream = cudaStreamPerThread; cfg.attrs = at; cfg.numAttrs = 1;
  cudaLaunchKernelEx(&cfg, main_kernel, P, M);
}
```
